```python
import torch

def _softmax(x, axis=-1):
    return torch.softmax(x, dim=axis)

def _gelu(x):
    return torch.nn.functional.gelu(x, approximate='tanh')

def _silu(x):
    return torch.nn.functional.silu(x)

def _sigmoid(x):
    return torch.sigmoid(x)

def _layernorm(x, axis=-1, eps=1e-05):
    m = x.mean(dim=axis, keepdim=True)
    v = x.var(dim=axis, keepdim=True, unbiased=False)
    return (x - m) / torch.sqrt(v + eps)

def _scatter_add(tgt, idx, src, axis=0):
    return tgt.clone().index_add_(axis, idx, src)

def _segment_sum(src, seg, n):
    out = torch.zeros((n,) + src.shape[1:], dtype=src.dtype)
    return out.index_add_(0, seg, src)

def _pad(x, pw):
    flat = tuple((v for pair in reversed(pw) for v in pair))
    return torch.nn.functional.pad(x, flat)
kernel_name = 'adaLN_cond__grouped_kv_mqa__dense_activation_relu__prompt'

def setup_inputs():

    _w = lambda a: (lambda t: t.to(torch.bfloat16) if t.is_floating_point() else t)(torch.as_tensor(a))

    def _A_setup():
        B, S, D, H = (1, 2048, 1024, 32)
        Dh = D // H
        return {'x': _w((lambda *s: torch.randn(*s, dtype=torch.bfloat16) * 0.05)(B, S, D)), 'wq': _w((lambda *s: torch.randn(*s, dtype=torch.bfloat16) * 0.05)(D, H * Dh)), 'wk': _w((lambda *s: torch.randn(*s, dtype=torch.bfloat16) * 0.05)(D, Dh)), 'wv': _w((lambda *s: torch.randn(*s, dtype=torch.bfloat16) * 0.05)(D, Dh)), 'wo': _w((lambda *s: torch.randn(*s, dtype=torch.bfloat16) * 0.05)(H * Dh, D))}
    _A_in = _A_setup()

    def _B_setup():
        B, S, D, Dff = (1, 2048, 1024, 3584)
        return {'x': _w((lambda *s: torch.randn(*s, dtype=torch.bfloat16) * 0.05)(B, S, D)), 'w1': _w((lambda *s: torch.randn(*s, dtype=torch.bfloat16) * 0.05)(D, Dff)), 'w2': _w((lambda *s: torch.randn(*s, dtype=torch.bfloat16) * 0.05)(Dff, D))}
    _B_in = _B_setup()
    return {'A_x': _A_in['x'], 'A_wq': _A_in['wq'], 'A_wk': _A_in['wk'], 'A_wv': _A_in['wv'], 'A_wo': _A_in['wo'], 'B_x': _B_in['x'], 'B_w1': _B_in['w1'], 'B_w2': _B_in['w2'], 'c': _w((lambda *s: torch.randn(*s, dtype=torch.bfloat16) * 0.2)(1, 1024) * 8.0), 'w_mod': _w((lambda *s: torch.randn(*s, dtype=torch.bfloat16) * 0.2)(1024, 6 * 1024) * 1024 ** (-0.5) * 8.0)}

def reference(A_x, A_wq, A_wk, A_wv, A_wo, B_x, B_w1, B_w2, c, w_mod):

    def _A_ref(x, wq, wk, wv, wo):
        B, S, D = x.shape
        H = 32
        Dh = D // H
        q = (lambda x, *d: x.permute(*d))((x @ wq).reshape(B, S, H, Dh), 0, 2, 1, 3)
        k = x @ wk
        v = x @ wv
        scores = torch.einsum('bhqd,bkd->bhqk', q, k) * Dh ** (-0.5)
        p = _softmax(scores, axis=-1)
        o = torch.einsum('bhqk,bkd->bhqd', p, v)
        return (lambda x, *d: x.permute(*d))(o, 0, 2, 1, 3).reshape(B, S, H * Dh) @ wo

    def _B_ref(x, w1, w2):
        h = torch.einsum('bsd,df->bsf', x, w1)
        zero = torch.zeros_like(h)
        h = torch.maximum(h, zero)
        return torch.einsum('bsf,fd->bsd', h, w2)
    x = A_x
    mod = (_silu(c) @ w_mod).reshape(c.shape[0], 6, 1, -1)
    sa, ca, ga, sb, cb, gb = (mod[:, 0].clone(), mod[:, 1].clone(), mod[:, 2].clone(), mod[:, 3].clone(), mod[:, 4].clone(), mod[:, 5].clone())
    h = _layernorm(x, axis=-1) * (1 + ca) + sa
    x = x + ga * _A_ref(h, A_wq, A_wk, A_wv, A_wo)
    h = _layernorm(x, axis=-1) * (1 + cb) + sb
    x = x + gb * _B_ref(h, B_w1, B_w2)
    return x
```

```cpp
#include <cuda_runtime.h>
#include <cuda_bf16.h>
#include <cuda.h>
#include <stdint.h>

namespace {

constexpr int SEQ = 2048, DM = 1024, DH = 32, DFF = 3584;
typedef __nv_bfloat16 bf16;

__device__ __align__(1024) float g_mod[6 * DM];
__device__ __align__(1024) float2 g_stats1[SEQ];
__device__ __align__(1024) bf16 g_h[SEQ * DM];
__device__ __align__(1024) bf16 g_q[SEQ * DM];
__device__ __align__(1024) bf16 g_k[SEQ * DH];
__device__ __align__(1024) bf16 g_vt[DH * SEQ];
__device__ __align__(1024) bf16 g_o[SEQ * DM];
__device__ __align__(1024) bf16 g_x1[SEQ * DM];
__device__ __align__(1024) float2 g_stats2[SEQ * 8];
__device__ __align__(1024) bf16 g_hff[SEQ * DFF];

__device__ __forceinline__ uint32_t smem_u32(const void* p) { return (uint32_t)__cvta_generic_to_shared(p); }

__device__ __forceinline__ void mbar_init(uint32_t bar, uint32_t count) {
  asm volatile("mbarrier.init.shared::cta.b64 [%0], %1;" ::"r"(bar), "r"(count) : "memory");
}
__device__ __forceinline__ void mbar_expect_tx(uint32_t bar, uint32_t bytes) {
  asm volatile("mbarrier.arrive.expect_tx.shared::cta.b64 _, [%0], %1;" ::"r"(bar), "r"(bytes) : "memory");
}
__device__ __forceinline__ void mbar_arrive(uint32_t bar) {
  asm volatile("mbarrier.arrive.shared::cta.b64 _, [%0];" ::"r"(bar) : "memory");
}
__device__ __forceinline__ void mbar_arrive_cluster(uint32_t bar, uint32_t cta) {
  asm volatile(
      "{\n.reg .b32 ra;\n"
      "mapa.shared::cluster.u32 ra, %0, %1;\n"
      "mbarrier.arrive.release.cluster.shared::cluster.b64 _, [ra];\n}\n" ::"r"(bar), "r"(cta)
      : "memory");
}
__device__ __forceinline__ bool mbar_try_wait(uint32_t bar, uint32_t parity) {
  uint32_t ok;
  asm volatile(
      "{\n.reg .pred p;\n"
      "mbarrier.try_wait.parity.shared::cta.b64 p, [%1], %2;\n"
      "selp.u32 %0, 1, 0, p;\n}\n"
      : "=r"(ok)
      : "r"(bar), "r"(parity)
      : "memory");
  return ok != 0;
}
__device__ __forceinline__ void mbar_wait(uint32_t bar, uint32_t parity) {
  uint32_t spins = 0;
  while (!mbar_try_wait(bar, parity)) {
    if (++spins > (1u << 24)) __trap();
  }
}
__device__ __forceinline__ void mbar_wait_cluster(uint32_t bar, uint32_t parity) {
  uint32_t spins = 0;
  while (true) {
    uint32_t ok;
    asm volatile(
        "{\n.reg .pred p;\n"
        "mbarrier.try_wait.parity.acquire.cluster.shared::cta.b64 p, [%1], %2;\n"
        "selp.u32 %0, 1, 0, p;\n}\n"
        : "=r"(ok)
        : "r"(bar), "r"(parity)
        : "memory");
    if (ok) break;
    if (++spins > (1u << 24)) __trap();
  }
}
__device__ __forceinline__ void fence_barrier_init() { asm volatile("fence.mbarrier_init.release.cluster;" ::: "memory"); }
__device__ __forceinline__ void fence_proxy_async() { asm volatile("fence.proxy.async.shared::cta;" ::: "memory"); }
__device__ __forceinline__ void cluster_sync_all() {
  asm volatile("barrier.cluster.arrive.release.aligned;\nbarrier.cluster.wait.acquire.aligned;" ::: "memory");
}
__device__ __forceinline__ void pdl_wait() { asm volatile("griddepcontrol.wait;" ::: "memory"); }
__device__ __forceinline__ void pdl_launch() { asm volatile("griddepcontrol.launch_dependents;" ::: "memory"); }
__device__ __forceinline__ void prefetch_tmap(const CUtensorMap* m) {
  asm volatile("prefetch.tensormap [%0];" ::"l"(reinterpret_cast<uint64_t>(m)) : "memory");
}
__device__ __forceinline__ void tma_2d(uint32_t dst, const CUtensorMap* m, uint32_t bar, int c0, int c1) {
  asm volatile(
      "cp.async.bulk.tensor.2d.shared::cluster.global.mbarrier::complete_tx::bytes [%0], [%1, {%3, %4}], [%2];" ::"r"(dst),
      "l"(reinterpret_cast<uint64_t>(m)), "r"(bar), "r"(c0), "r"(c1)
      : "memory");
}
__device__ __forceinline__ void tma_2d_mc(uint32_t dst, const CUtensorMap* m, uint32_t bar, int c0, int c1, uint16_t mask) {
  asm volatile(
      "cp.async.bulk.tensor.2d.shared::cluster.global.mbarrier::complete_tx::bytes.multicast::cluster [%0], [%1, {%3, %4}], "
      "[%2], %5;" ::"r"(dst),
      "l"(reinterpret_cast<uint64_t>(m)), "r"(bar), "r"(c0), "r"(c1), "h"(mask)
      : "memory");
}
__device__ __forceinline__ void tma_3d(uint32_t dst, const CUtensorMap* m, uint32_t bar, int c0, int c1, int c2) {
  asm volatile(
      "cp.async.bulk.tensor.3d.shared::cluster.global.mbarrier::complete_tx::bytes [%0], [%1, {%3, %4, %5}], [%2];" ::"r"(dst),
      "l"(reinterpret_cast<uint64_t>(m)), "r"(bar), "r"(c0), "r"(c1), "r"(c2)
      : "memory");
}
__device__ __forceinline__ void tma_3d_mc(uint32_t dst, const CUtensorMap* m, uint32_t bar, int c0, int c1, int c2,
                                          uint16_t mask) {
  asm volatile(
      "cp.async.bulk.tensor.3d.shared::cluster.global.mbarrier::complete_tx::bytes.multicast::cluster [%0], [%1, {%3, %4, "
      "%5}], [%2], %6;" ::"r"(dst),
      "l"(reinterpret_cast<uint64_t>(m)), "r"(bar), "r"(c0), "r"(c1), "r"(c2), "h"(mask)
      : "memory");
}
__device__ __forceinline__ void wgmma_fence() { asm volatile("wgmma.fence.sync.aligned;" ::: "memory"); }
__device__ __forceinline__ void wgmma_commit() { asm volatile("wgmma.commit_group.sync.aligned;" ::: "memory"); }
template <int N>
__device__ __forceinline__ void wgmma_wait() {
  asm volatile("wgmma.wait_group.sync.aligned %0;" ::"n"(N) : "memory");
}
template <int R>
__device__ __forceinline__ void reg_alloc() { asm volatile("setmaxnreg.inc.sync.aligned.u32 %0;" ::"n"(R)); }
template <int R>
__device__ __forceinline__ void reg_dealloc() { asm volatile("setmaxnreg.dec.sync.aligned.u32 %0;" ::"n"(R)); }

template <int N>
__device__ __forceinline__ void fence_regs(float (&d)[N]) {
#pragma unroll
  for (int i = 0; i < N; i++) asm volatile("" : "+f"(d[i])::"memory");
}

__device__ __forceinline__ uint64_t make_desc(uint32_t addr, uint32_t lbo, uint32_t sbo, uint32_t swz) {
  return (uint64_t)((addr & 0x3FFFF) >> 4) | ((uint64_t)((lbo & 0x3FFFF) >> 4) << 16) |
         ((uint64_t)((sbo & 0x3FFFF) >> 4) << 32) | ((uint64_t)swz << 62);
}
__device__ __forceinline__ uint32_t pack_bf16(float lo, float hi) {
  uint32_t r;
  asm("cvt.rn.bf16x2.f32 %0, %1, %2;" : "=r"(r) : "f"(hi), "f"(lo));
  return r;
}
__device__ __forceinline__ float bf16_lo(uint32_t v) { return __uint_as_float(v << 16); }
__device__ __forceinline__ float bf16_hi(uint32_t v) { return __uint_as_float(v & 0xFFFF0000u); }
__device__ __forceinline__ float round_bf16(float x) { return __bfloat162float(__float2bfloat16_rn(x)); }
__device__ __forceinline__ float ex2(float x) {
  float y;
  asm("ex2.approx.ftz.f32 %0, %1;" : "=f"(y) : "f"(x));
  return y;
}

__device__ __forceinline__ void wgmma_ss_n8_t1(float (&d)[4], uint64_t da, uint64_t db, int sd) {
  asm volatile("{\n.reg .pred p;\nsetp.ne.b32 p, %6, 0;\n"
    "wgmma.mma_async.sync.aligned.m64n8k16.f32.bf16.bf16 {%0, %1, %2, %3}, %4, %5, p, 1, 1, 0, 1;\n}\n"
    : "+f"(d[0]), "+f"(d[1]), "+f"(d[2]), "+f"(d[3])
    : "l"(da), "l"(db), "r"(sd));
}

__device__ __forceinline__ void wgmma_rs_n8_t1(float (&d)[4], uint32_t a0, uint32_t a1, uint32_t a2, uint32_t a3, uint64_t db, int sd) {
  asm volatile("{\n.reg .pred p;\nsetp.ne.b32 p, %9, 0;\n"
    "wgmma.mma_async.sync.aligned.m64n8k16.f32.bf16.bf16 {%0, %1, %2, %3}, {%4, %5, %6, %7}, %8, p, 1, 1, 1;\n}\n"
    : "+f"(d[0]), "+f"(d[1]), "+f"(d[2]), "+f"(d[3])
    : "r"(a0), "r"(a1), "r"(a2), "r"(a3), "l"(db), "r"(sd));
}

__device__ __forceinline__ void wgmma_ss_n128_t1(float (&d)[64], uint64_t da, uint64_t db, int sd) {
  asm volatile("{\n.reg .pred p;\nsetp.ne.b32 p, %66, 0;\n"
    "wgmma.mma_async.sync.aligned.m64n128k16.f32.bf16.bf16 {%0, %1, %2, %3, %4, %5, %6, %7, %8, %9, %10, %11, %12, %13, %14, %15, %16, %17, %18, %19, %20, %21, %22, %23, %24, %25, %26, %27, %28, %29, %30, %31, %32, %33, %34, %35, %36, %37, %38, %39, %40, %41, %42, %43, %44, %45, %46, %47, %48, %49, %50, %51, %52, %53, %54, %55, %56, %57, %58, %59, %60, %61, %62, %63}, %64, %65, p, 1, 1, 0, 1;\n}\n"
    : "+f"(d[0]), "+f"(d[1]), "+f"(d[2]), "+f"(d[3]), "+f"(d[4]), "+f"(d[5]), "+f"(d[6]), "+f"(d[7]), "+f"(d[8]), "+f"(d[9]), "+f"(d[10]), "+f"(d[11]), "+f"(d[12]), "+f"(d[13]), "+f"(d[14]), "+f"(d[15]), "+f"(d[16]), "+f"(d[17]), "+f"(d[18]), "+f"(d[19]), "+f"(d[20]), "+f"(d[21]), "+f"(d[22]), "+f"(d[23]), "+f"(d[24]), "+f"(d[25]), "+f"(d[26]), "+f"(d[27]), "+f"(d[28]), "+f"(d[29]), "+f"(d[30]), "+f"(d[31]), "+f"(d[32]), "+f"(d[33]), "+f"(d[34]), "+f"(d[35]), "+f"(d[36]), "+f"(d[37]), "+f"(d[38]), "+f"(d[39]), "+f"(d[40]), "+f"(d[41]), "+f"(d[42]), "+f"(d[43]), "+f"(d[44]), "+f"(d[45]), "+f"(d[46]), "+f"(d[47]), "+f"(d[48]), "+f"(d[49]), "+f"(d[50]), "+f"(d[51]), "+f"(d[52]), "+f"(d[53]), "+f"(d[54]), "+f"(d[55]), "+f"(d[56]), "+f"(d[57]), "+f"(d[58]), "+f"(d[59]), "+f"(d[60]), "+f"(d[61]), "+f"(d[62]), "+f"(d[63])
    : "l"(da), "l"(db), "r"(sd));
}

__device__ __forceinline__ void wgmma_rs_n128_t1(float (&d)[64], uint32_t a0, uint32_t a1, uint32_t a2, uint32_t a3, uint64_t db, int sd) {
  asm volatile("{\n.reg .pred p;\nsetp.ne.b32 p, %69, 0;\n"
    "wgmma.mma_async.sync.aligned.m64n128k16.f32.bf16.bf16 {%0, %1, %2, %3, %4, %5, %6, %7, %8, %9, %10, %11, %12, %13, %14, %15, %16, %17, %18, %19, %20, %21, %22, %23, %24, %25, %26, %27, %28, %29, %30, %31, %32, %33, %34, %35, %36, %37, %38, %39, %40, %41, %42, %43, %44, %45, %46, %47, %48, %49, %50, %51, %52, %53, %54, %55, %56, %57, %58, %59, %60, %61, %62, %63}, {%64, %65, %66, %67}, %68, p, 1, 1, 1;\n}\n"
    : "+f"(d[0]), "+f"(d[1]), "+f"(d[2]), "+f"(d[3]), "+f"(d[4]), "+f"(d[5]), "+f"(d[6]), "+f"(d[7]), "+f"(d[8]), "+f"(d[9]), "+f"(d[10]), "+f"(d[11]), "+f"(d[12]), "+f"(d[13]), "+f"(d[14]), "+f"(d[15]), "+f"(d[16]), "+f"(d[17]), "+f"(d[18]), "+f"(d[19]), "+f"(d[20]), "+f"(d[21]), "+f"(d[22]), "+f"(d[23]), "+f"(d[24]), "+f"(d[25]), "+f"(d[26]), "+f"(d[27]), "+f"(d[28]), "+f"(d[29]), "+f"(d[30]), "+f"(d[31]), "+f"(d[32]), "+f"(d[33]), "+f"(d[34]), "+f"(d[35]), "+f"(d[36]), "+f"(d[37]), "+f"(d[38]), "+f"(d[39]), "+f"(d[40]), "+f"(d[41]), "+f"(d[42]), "+f"(d[43]), "+f"(d[44]), "+f"(d[45]), "+f"(d[46]), "+f"(d[47]), "+f"(d[48]), "+f"(d[49]), "+f"(d[50]), "+f"(d[51]), "+f"(d[52]), "+f"(d[53]), "+f"(d[54]), "+f"(d[55]), "+f"(d[56]), "+f"(d[57]), "+f"(d[58]), "+f"(d[59]), "+f"(d[60]), "+f"(d[61]), "+f"(d[62]), "+f"(d[63])
    : "r"(a0), "r"(a1), "r"(a2), "r"(a3), "l"(db), "r"(sd));
}

__device__ __forceinline__ void wgmma_ss_n224_t1(float (&d)[112], uint64_t da, uint64_t db, int sd) {
  asm volatile("{\n.reg .pred p;\nsetp.ne.b32 p, %114, 0;\n"
    "wgmma.mma_async.sync.aligned.m64n224k16.f32.bf16.bf16 {%0, %1, %2, %3, %4, %5, %6, %7, %8, %9, %10, %11, %12, %13, %14, %15, %16, %17, %18, %19, %20, %21, %22, %23, %24, %25, %26, %27, %28, %29, %30, %31, %32, %33, %34, %35, %36, %37, %38, %39, %40, %41, %42, %43, %44, %45, %46, %47, %48, %49, %50, %51, %52, %53, %54, %55, %56, %57, %58, %59, %60, %61, %62, %63, %64, %65, %66, %67, %68, %69, %70, %71, %72, %73, %74, %75, %76, %77, %78, %79, %80, %81, %82, %83, %84, %85, %86, %87, %88, %89, %90, %91, %92, %93, %94, %95, %96, %97, %98, %99, %100, %101, %102, %103, %104, %105, %106, %107, %108, %109, %110, %111}, %112, %113, p, 1, 1, 0, 1;\n}\n"
    : "+f"(d[0]), "+f"(d[1]), "+f"(d[2]), "+f"(d[3]), "+f"(d[4]), "+f"(d[5]), "+f"(d[6]), "+f"(d[7]), "+f"(d[8]), "+f"(d[9]), "+f"(d[10]), "+f"(d[11]), "+f"(d[12]), "+f"(d[13]), "+f"(d[14]), "+f"(d[15]), "+f"(d[16]), "+f"(d[17]), "+f"(d[18]), "+f"(d[19]), "+f"(d[20]), "+f"(d[21]), "+f"(d[22]), "+f"(d[23]), "+f"(d[24]), "+f"(d[25]), "+f"(d[26]), "+f"(d[27]), "+f"(d[28]), "+f"(d[29]), "+f"(d[30]), "+f"(d[31]), "+f"(d[32]), "+f"(d[33]), "+f"(d[34]), "+f"(d[35]), "+f"(d[36]), "+f"(d[37]), "+f"(d[38]), "+f"(d[39]), "+f"(d[40]), "+f"(d[41]), "+f"(d[42]), "+f"(d[43]), "+f"(d[44]), "+f"(d[45]), "+f"(d[46]), "+f"(d[47]), "+f"(d[48]), "+f"(d[49]), "+f"(d[50]), "+f"(d[51]), "+f"(d[52]), "+f"(d[53]), "+f"(d[54]), "+f"(d[55]), "+f"(d[56]), "+f"(d[57]), "+f"(d[58]), "+f"(d[59]), "+f"(d[60]), "+f"(d[61]), "+f"(d[62]), "+f"(d[63]), "+f"(d[64]), "+f"(d[65]), "+f"(d[66]), "+f"(d[67]), "+f"(d[68]), "+f"(d[69]), "+f"(d[70]), "+f"(d[71]), "+f"(d[72]), "+f"(d[73]), "+f"(d[74]), "+f"(d[75]), "+f"(d[76]), "+f"(d[77]), "+f"(d[78]), "+f"(d[79]), "+f"(d[80]), "+f"(d[81]), "+f"(d[82]), "+f"(d[83]), "+f"(d[84]), "+f"(d[85]), "+f"(d[86]), "+f"(d[87]), "+f"(d[88]), "+f"(d[89]), "+f"(d[90]), "+f"(d[91]), "+f"(d[92]), "+f"(d[93]), "+f"(d[94]), "+f"(d[95]), "+f"(d[96]), "+f"(d[97]), "+f"(d[98]), "+f"(d[99]), "+f"(d[100]), "+f"(d[101]), "+f"(d[102]), "+f"(d[103]), "+f"(d[104]), "+f"(d[105]), "+f"(d[106]), "+f"(d[107]), "+f"(d[108]), "+f"(d[109]), "+f"(d[110]), "+f"(d[111])
    : "l"(da), "l"(db), "r"(sd));
}

__device__ __forceinline__ void wgmma_rs_n224_t1(float (&d)[112], uint32_t a0, uint32_t a1, uint32_t a2, uint32_t a3, uint64_t db, int sd) {
  asm volatile("{\n.reg .pred p;\nsetp.ne.b32 p, %117, 0;\n"
    "wgmma.mma_async.sync.aligned.m64n224k16.f32.bf16.bf16 {%0, %1, %2, %3, %4, %5, %6, %7, %8, %9, %10, %11, %12, %13, %14, %15, %16, %17, %18, %19, %20, %21, %22, %23, %24, %25, %26, %27, %28, %29, %30, %31, %32, %33, %34, %35, %36, %37, %38, %39, %40, %41, %42, %43, %44, %45, %46, %47, %48, %49, %50, %51, %52, %53, %54, %55, %56, %57, %58, %59, %60, %61, %62, %63, %64, %65, %66, %67, %68, %69, %70, %71, %72, %73, %74, %75, %76, %77, %78, %79, %80, %81, %82, %83, %84, %85, %86, %87, %88, %89, %90, %91, %92, %93, %94, %95, %96, %97, %98, %99, %100, %101, %102, %103, %104, %105, %106, %107, %108, %109, %110, %111}, {%112, %113, %114, %115}, %116, p, 1, 1, 1;\n}\n"
    : "+f"(d[0]), "+f"(d[1]), "+f"(d[2]), "+f"(d[3]), "+f"(d[4]), "+f"(d[5]), "+f"(d[6]), "+f"(d[7]), "+f"(d[8]), "+f"(d[9]), "+f"(d[10]), "+f"(d[11]), "+f"(d[12]), "+f"(d[13]), "+f"(d[14]), "+f"(d[15]), "+f"(d[16]), "+f"(d[17]), "+f"(d[18]), "+f"(d[19]), "+f"(d[20]), "+f"(d[21]), "+f"(d[22]), "+f"(d[23]), "+f"(d[24]), "+f"(d[25]), "+f"(d[26]), "+f"(d[27]), "+f"(d[28]), "+f"(d[29]), "+f"(d[30]), "+f"(d[31]), "+f"(d[32]), "+f"(d[33]), "+f"(d[34]), "+f"(d[35]), "+f"(d[36]), "+f"(d[37]), "+f"(d[38]), "+f"(d[39]), "+f"(d[40]), "+f"(d[41]), "+f"(d[42]), "+f"(d[43]), "+f"(d[44]), "+f"(d[45]), "+f"(d[46]), "+f"(d[47]), "+f"(d[48]), "+f"(d[49]), "+f"(d[50]), "+f"(d[51]), "+f"(d[52]), "+f"(d[53]), "+f"(d[54]), "+f"(d[55]), "+f"(d[56]), "+f"(d[57]), "+f"(d[58]), "+f"(d[59]), "+f"(d[60]), "+f"(d[61]), "+f"(d[62]), "+f"(d[63]), "+f"(d[64]), "+f"(d[65]), "+f"(d[66]), "+f"(d[67]), "+f"(d[68]), "+f"(d[69]), "+f"(d[70]), "+f"(d[71]), "+f"(d[72]), "+f"(d[73]), "+f"(d[74]), "+f"(d[75]), "+f"(d[76]), "+f"(d[77]), "+f"(d[78]), "+f"(d[79]), "+f"(d[80]), "+f"(d[81]), "+f"(d[82]), "+f"(d[83]), "+f"(d[84]), "+f"(d[85]), "+f"(d[86]), "+f"(d[87]), "+f"(d[88]), "+f"(d[89]), "+f"(d[90]), "+f"(d[91]), "+f"(d[92]), "+f"(d[93]), "+f"(d[94]), "+f"(d[95]), "+f"(d[96]), "+f"(d[97]), "+f"(d[98]), "+f"(d[99]), "+f"(d[100]), "+f"(d[101]), "+f"(d[102]), "+f"(d[103]), "+f"(d[104]), "+f"(d[105]), "+f"(d[106]), "+f"(d[107]), "+f"(d[108]), "+f"(d[109]), "+f"(d[110]), "+f"(d[111])
    : "r"(a0), "r"(a1), "r"(a2), "r"(a3), "l"(db), "r"(sd));
}

__device__ __forceinline__ void wgmma_ss_n256_t1(float (&d)[128], uint64_t da, uint64_t db, int sd) {
  asm volatile("{\n.reg .pred p;\nsetp.ne.b32 p, %130, 0;\n"
    "wgmma.mma_async.sync.aligned.m64n256k16.f32.bf16.bf16 {%0, %1, %2, %3, %4, %5, %6, %7, %8, %9, %10, %11, %12, %13, %14, %15, %16, %17, %18, %19, %20, %21, %22, %23, %24, %25, %26, %27, %28, %29, %30, %31, %32, %33, %34, %35, %36, %37, %38, %39, %40, %41, %42, %43, %44, %45, %46, %47, %48, %49, %50, %51, %52, %53, %54, %55, %56, %57, %58, %59, %60, %61, %62, %63, %64, %65, %66, %67, %68, %69, %70, %71, %72, %73, %74, %75, %76, %77, %78, %79, %80, %81, %82, %83, %84, %85, %86, %87, %88, %89, %90, %91, %92, %93, %94, %95, %96, %97, %98, %99, %100, %101, %102, %103, %104, %105, %106, %107, %108, %109, %110, %111, %112, %113, %114, %115, %116, %117, %118, %119, %120, %121, %122, %123, %124, %125, %126, %127}, %128, %129, p, 1, 1, 0, 1;\n}\n"
    : "+f"(d[0]), "+f"(d[1]), "+f"(d[2]), "+f"(d[3]), "+f"(d[4]), "+f"(d[5]), "+f"(d[6]), "+f"(d[7]), "+f"(d[8]), "+f"(d[9]), "+f"(d[10]), "+f"(d[11]), "+f"(d[12]), "+f"(d[13]), "+f"(d[14]), "+f"(d[15]), "+f"(d[16]), "+f"(d[17]), "+f"(d[18]), "+f"(d[19]), "+f"(d[20]), "+f"(d[21]), "+f"(d[22]), "+f"(d[23]), "+f"(d[24]), "+f"(d[25]), "+f"(d[26]), "+f"(d[27]), "+f"(d[28]), "+f"(d[29]), "+f"(d[30]), "+f"(d[31]), "+f"(d[32]), "+f"(d[33]), "+f"(d[34]), "+f"(d[35]), "+f"(d[36]), "+f"(d[37]), "+f"(d[38]), "+f"(d[39]), "+f"(d[40]), "+f"(d[41]), "+f"(d[42]), "+f"(d[43]), "+f"(d[44]), "+f"(d[45]), "+f"(d[46]), "+f"(d[47]), "+f"(d[48]), "+f"(d[49]), "+f"(d[50]), "+f"(d[51]), "+f"(d[52]), "+f"(d[53]), "+f"(d[54]), "+f"(d[55]), "+f"(d[56]), "+f"(d[57]), "+f"(d[58]), "+f"(d[59]), "+f"(d[60]), "+f"(d[61]), "+f"(d[62]), "+f"(d[63]), "+f"(d[64]), "+f"(d[65]), "+f"(d[66]), "+f"(d[67]), "+f"(d[68]), "+f"(d[69]), "+f"(d[70]), "+f"(d[71]), "+f"(d[72]), "+f"(d[73]), "+f"(d[74]), "+f"(d[75]), "+f"(d[76]), "+f"(d[77]), "+f"(d[78]), "+f"(d[79]), "+f"(d[80]), "+f"(d[81]), "+f"(d[82]), "+f"(d[83]), "+f"(d[84]), "+f"(d[85]), "+f"(d[86]), "+f"(d[87]), "+f"(d[88]), "+f"(d[89]), "+f"(d[90]), "+f"(d[91]), "+f"(d[92]), "+f"(d[93]), "+f"(d[94]), "+f"(d[95]), "+f"(d[96]), "+f"(d[97]), "+f"(d[98]), "+f"(d[99]), "+f"(d[100]), "+f"(d[101]), "+f"(d[102]), "+f"(d[103]), "+f"(d[104]), "+f"(d[105]), "+f"(d[106]), "+f"(d[107]), "+f"(d[108]), "+f"(d[109]), "+f"(d[110]), "+f"(d[111]), "+f"(d[112]), "+f"(d[113]), "+f"(d[114]), "+f"(d[115]), "+f"(d[116]), "+f"(d[117]), "+f"(d[118]), "+f"(d[119]), "+f"(d[120]), "+f"(d[121]), "+f"(d[122]), "+f"(d[123]), "+f"(d[124]), "+f"(d[125]), "+f"(d[126]), "+f"(d[127])
    : "l"(da), "l"(db), "r"(sd));
}

__device__ __forceinline__ void wgmma_rs_n256_t1(float (&d)[128], uint32_t a0, uint32_t a1, uint32_t a2, uint32_t a3, uint64_t db, int sd) {
  asm volatile("{\n.reg .pred p;\nsetp.ne.b32 p, %133, 0;\n"
    "wgmma.mma_async.sync.aligned.m64n256k16.f32.bf16.bf16 {%0, %1, %2, %3, %4, %5, %6, %7, %8, %9, %10, %11, %12, %13, %14, %15, %16, %17, %18, %19, %20, %21, %22, %23, %24, %25, %26, %27, %28, %29, %30, %31, %32, %33, %34, %35, %36, %37, %38, %39, %40, %41, %42, %43, %44, %45, %46, %47, %48, %49, %50, %51, %52, %53, %54, %55, %56, %57, %58, %59, %60, %61, %62, %63, %64, %65, %66, %67, %68, %69, %70, %71, %72, %73, %74, %75, %76, %77, %78, %79, %80, %81, %82, %83, %84, %85, %86, %87, %88, %89, %90, %91, %92, %93, %94, %95, %96, %97, %98, %99, %100, %101, %102, %103, %104, %105, %106, %107, %108, %109, %110, %111, %112, %113, %114, %115, %116, %117, %118, %119, %120, %121, %122, %123, %124, %125, %126, %127}, {%128, %129, %130, %131}, %132, p, 1, 1, 1;\n}\n"
    : "+f"(d[0]), "+f"(d[1]), "+f"(d[2]), "+f"(d[3]), "+f"(d[4]), "+f"(d[5]), "+f"(d[6]), "+f"(d[7]), "+f"(d[8]), "+f"(d[9]), "+f"(d[10]), "+f"(d[11]), "+f"(d[12]), "+f"(d[13]), "+f"(d[14]), "+f"(d[15]), "+f"(d[16]), "+f"(d[17]), "+f"(d[18]), "+f"(d[19]), "+f"(d[20]), "+f"(d[21]), "+f"(d[22]), "+f"(d[23]), "+f"(d[24]), "+f"(d[25]), "+f"(d[26]), "+f"(d[27]), "+f"(d[28]), "+f"(d[29]), "+f"(d[30]), "+f"(d[31]), "+f"(d[32]), "+f"(d[33]), "+f"(d[34]), "+f"(d[35]), "+f"(d[36]), "+f"(d[37]), "+f"(d[38]), "+f"(d[39]), "+f"(d[40]), "+f"(d[41]), "+f"(d[42]), "+f"(d[43]), "+f"(d[44]), "+f"(d[45]), "+f"(d[46]), "+f"(d[47]), "+f"(d[48]), "+f"(d[49]), "+f"(d[50]), "+f"(d[51]), "+f"(d[52]), "+f"(d[53]), "+f"(d[54]), "+f"(d[55]), "+f"(d[56]), "+f"(d[57]), "+f"(d[58]), "+f"(d[59]), "+f"(d[60]), "+f"(d[61]), "+f"(d[62]), "+f"(d[63]), "+f"(d[64]), "+f"(d[65]), "+f"(d[66]), "+f"(d[67]), "+f"(d[68]), "+f"(d[69]), "+f"(d[70]), "+f"(d[71]), "+f"(d[72]), "+f"(d[73]), "+f"(d[74]), "+f"(d[75]), "+f"(d[76]), "+f"(d[77]), "+f"(d[78]), "+f"(d[79]), "+f"(d[80]), "+f"(d[81]), "+f"(d[82]), "+f"(d[83]), "+f"(d[84]), "+f"(d[85]), "+f"(d[86]), "+f"(d[87]), "+f"(d[88]), "+f"(d[89]), "+f"(d[90]), "+f"(d[91]), "+f"(d[92]), "+f"(d[93]), "+f"(d[94]), "+f"(d[95]), "+f"(d[96]), "+f"(d[97]), "+f"(d[98]), "+f"(d[99]), "+f"(d[100]), "+f"(d[101]), "+f"(d[102]), "+f"(d[103]), "+f"(d[104]), "+f"(d[105]), "+f"(d[106]), "+f"(d[107]), "+f"(d[108]), "+f"(d[109]), "+f"(d[110]), "+f"(d[111]), "+f"(d[112]), "+f"(d[113]), "+f"(d[114]), "+f"(d[115]), "+f"(d[116]), "+f"(d[117]), "+f"(d[118]), "+f"(d[119]), "+f"(d[120]), "+f"(d[121]), "+f"(d[122]), "+f"(d[123]), "+f"(d[124]), "+f"(d[125]), "+f"(d[126]), "+f"(d[127])
    : "r"(a0), "r"(a1), "r"(a2), "r"(a3), "l"(db), "r"(sd));
}

__device__ __forceinline__ void wgmma_ss_n64_t0(float (&d)[32], uint64_t da, uint64_t db, int sd) {
  asm volatile("{\n.reg .pred p;\nsetp.ne.b32 p, %34, 0;\n"
    "wgmma.mma_async.sync.aligned.m64n64k16.f32.bf16.bf16 {%0, %1, %2, %3, %4, %5, %6, %7, %8, %9, %10, %11, %12, %13, %14, %15, %16, %17, %18, %19, %20, %21, %22, %23, %24, %25, %26, %27, %28, %29, %30, %31}, %32, %33, p, 1, 1, 0, 0;\n}\n"
    : "+f"(d[0]), "+f"(d[1]), "+f"(d[2]), "+f"(d[3]), "+f"(d[4]), "+f"(d[5]), "+f"(d[6]), "+f"(d[7]), "+f"(d[8]), "+f"(d[9]), "+f"(d[10]), "+f"(d[11]), "+f"(d[12]), "+f"(d[13]), "+f"(d[14]), "+f"(d[15]), "+f"(d[16]), "+f"(d[17]), "+f"(d[18]), "+f"(d[19]), "+f"(d[20]), "+f"(d[21]), "+f"(d[22]), "+f"(d[23]), "+f"(d[24]), "+f"(d[25]), "+f"(d[26]), "+f"(d[27]), "+f"(d[28]), "+f"(d[29]), "+f"(d[30]), "+f"(d[31])
    : "l"(da), "l"(db), "r"(sd));
}

__device__ __forceinline__ void wgmma_ss_z_n64_t0(float (&d)[32], uint64_t da, uint64_t db) {
  asm volatile("{\n.reg .pred p;\nsetp.ne.b32 p, 0, 0;\n"
    "wgmma.mma_async.sync.aligned.m64n64k16.f32.bf16.bf16 {%0, %1, %2, %3, %4, %5, %6, %7, %8, %9, %10, %11, %12, %13, %14, %15, %16, %17, %18, %19, %20, %21, %22, %23, %24, %25, %26, %27, %28, %29, %30, %31}, %32, %33, p, 1, 1, 0, 0;\n}\n"
    : "=f"(d[0]), "=f"(d[1]), "=f"(d[2]), "=f"(d[3]), "=f"(d[4]), "=f"(d[5]), "=f"(d[6]), "=f"(d[7]), "=f"(d[8]), "=f"(d[9]), "=f"(d[10]), "=f"(d[11]), "=f"(d[12]), "=f"(d[13]), "=f"(d[14]), "=f"(d[15]), "=f"(d[16]), "=f"(d[17]), "=f"(d[18]), "=f"(d[19]), "=f"(d[20]), "=f"(d[21]), "=f"(d[22]), "=f"(d[23]), "=f"(d[24]), "=f"(d[25]), "=f"(d[26]), "=f"(d[27]), "=f"(d[28]), "=f"(d[29]), "=f"(d[30]), "=f"(d[31])
    : "l"(da), "l"(db));
}

__device__ __forceinline__ void wgmma_ss_n128_t0(float (&d)[64], uint64_t da, uint64_t db, int sd) {
  asm volatile("{\n.reg .pred p;\nsetp.ne.b32 p, %66, 0;\n"
    "wgmma.mma_async.sync.aligned.m64n128k16.f32.bf16.bf16 {%0, %1, %2, %3, %4, %5, %6, %7, %8, %9, %10, %11, %12, %13, %14, %15, %16, %17, %18, %19, %20, %21, %22, %23, %24, %25, %26, %27, %28, %29, %30, %31, %32, %33, %34, %35, %36, %37, %38, %39, %40, %41, %42, %43, %44, %45, %46, %47, %48, %49, %50, %51, %52, %53, %54, %55, %56, %57, %58, %59, %60, %61, %62, %63}, %64, %65, p, 1, 1, 0, 0;\n}\n"
    : "+f"(d[0]), "+f"(d[1]), "+f"(d[2]), "+f"(d[3]), "+f"(d[4]), "+f"(d[5]), "+f"(d[6]), "+f"(d[7]), "+f"(d[8]), "+f"(d[9]), "+f"(d[10]), "+f"(d[11]), "+f"(d[12]), "+f"(d[13]), "+f"(d[14]), "+f"(d[15]), "+f"(d[16]), "+f"(d[17]), "+f"(d[18]), "+f"(d[19]), "+f"(d[20]), "+f"(d[21]), "+f"(d[22]), "+f"(d[23]), "+f"(d[24]), "+f"(d[25]), "+f"(d[26]), "+f"(d[27]), "+f"(d[28]), "+f"(d[29]), "+f"(d[30]), "+f"(d[31]), "+f"(d[32]), "+f"(d[33]), "+f"(d[34]), "+f"(d[35]), "+f"(d[36]), "+f"(d[37]), "+f"(d[38]), "+f"(d[39]), "+f"(d[40]), "+f"(d[41]), "+f"(d[42]), "+f"(d[43]), "+f"(d[44]), "+f"(d[45]), "+f"(d[46]), "+f"(d[47]), "+f"(d[48]), "+f"(d[49]), "+f"(d[50]), "+f"(d[51]), "+f"(d[52]), "+f"(d[53]), "+f"(d[54]), "+f"(d[55]), "+f"(d[56]), "+f"(d[57]), "+f"(d[58]), "+f"(d[59]), "+f"(d[60]), "+f"(d[61]), "+f"(d[62]), "+f"(d[63])
    : "l"(da), "l"(db), "r"(sd));
}

__device__ __forceinline__ void wgmma_ss_z_n128_t0(float (&d)[64], uint64_t da, uint64_t db) {
  asm volatile("{\n.reg .pred p;\nsetp.ne.b32 p, 0, 0;\n"
    "wgmma.mma_async.sync.aligned.m64n128k16.f32.bf16.bf16 {%0, %1, %2, %3, %4, %5, %6, %7, %8, %9, %10, %11, %12, %13, %14, %15, %16, %17, %18, %19, %20, %21, %22, %23, %24, %25, %26, %27, %28, %29, %30, %31, %32, %33, %34, %35, %36, %37, %38, %39, %40, %41, %42, %43, %44, %45, %46, %47, %48, %49, %50, %51, %52, %53, %54, %55, %56, %57, %58, %59, %60, %61, %62, %63}, %64, %65, p, 1, 1, 0, 0;\n}\n"
    : "=f"(d[0]), "=f"(d[1]), "=f"(d[2]), "=f"(d[3]), "=f"(d[4]), "=f"(d[5]), "=f"(d[6]), "=f"(d[7]), "=f"(d[8]), "=f"(d[9]), "=f"(d[10]), "=f"(d[11]), "=f"(d[12]), "=f"(d[13]), "=f"(d[14]), "=f"(d[15]), "=f"(d[16]), "=f"(d[17]), "=f"(d[18]), "=f"(d[19]), "=f"(d[20]), "=f"(d[21]), "=f"(d[22]), "=f"(d[23]), "=f"(d[24]), "=f"(d[25]), "=f"(d[26]), "=f"(d[27]), "=f"(d[28]), "=f"(d[29]), "=f"(d[30]), "=f"(d[31]), "=f"(d[32]), "=f"(d[33]), "=f"(d[34]), "=f"(d[35]), "=f"(d[36]), "=f"(d[37]), "=f"(d[38]), "=f"(d[39]), "=f"(d[40]), "=f"(d[41]), "=f"(d[42]), "=f"(d[43]), "=f"(d[44]), "=f"(d[45]), "=f"(d[46]), "=f"(d[47]), "=f"(d[48]), "=f"(d[49]), "=f"(d[50]), "=f"(d[51]), "=f"(d[52]), "=f"(d[53]), "=f"(d[54]), "=f"(d[55]), "=f"(d[56]), "=f"(d[57]), "=f"(d[58]), "=f"(d[59]), "=f"(d[60]), "=f"(d[61]), "=f"(d[62]), "=f"(d[63])
    : "l"(da), "l"(db));
}

__device__ __forceinline__ void wgmma_rs_n40_t0(float (&d)[20], uint32_t a0, uint32_t a1, uint32_t a2, uint32_t a3, uint64_t db, int sd) {
  asm volatile("{\n.reg .pred p;\nsetp.ne.b32 p, %25, 0;\n"
    "wgmma.mma_async.sync.aligned.m64n40k16.f32.bf16.bf16 {%0, %1, %2, %3, %4, %5, %6, %7, %8, %9, %10, %11, %12, %13, %14, %15, %16, %17, %18, %19}, {%20, %21, %22, %23}, %24, p, 1, 1, 0;\n}\n"
    : "+f"(d[0]), "+f"(d[1]), "+f"(d[2]), "+f"(d[3]), "+f"(d[4]), "+f"(d[5]), "+f"(d[6]), "+f"(d[7]), "+f"(d[8]), "+f"(d[9]), "+f"(d[10]), "+f"(d[11]), "+f"(d[12]), "+f"(d[13]), "+f"(d[14]), "+f"(d[15]), "+f"(d[16]), "+f"(d[17]), "+f"(d[18]), "+f"(d[19])
    : "r"(a0), "r"(a1), "r"(a2), "r"(a3), "l"(db), "r"(sd));
}

template <int N>
struct WG;
template <>
struct WG<128> {
  static __device__ __forceinline__ void ss(float (&d)[64], uint64_t a, uint64_t b, int sd) { wgmma_ss_n128_t1(d, a, b, sd); }
};
template <>
struct WG<224> {
  static __device__ __forceinline__ void ss(float (&d)[112], uint64_t a, uint64_t b, int sd) { wgmma_ss_n224_t1(d, a, b, sd); }
};
template <>
struct WG<256> {
  static __device__ __forceinline__ void ss(float (&d)[128], uint64_t a, uint64_t b, int sd) { wgmma_ss_n256_t1(d, a, b, sd); }
};

__global__ void __cluster_dims__(4, 1, 1) __launch_bounds__(256)
    mod_kernel(const bf16* __restrict__ c, const bf16* __restrict__ wmod, const bf16* __restrict__ x) {
  __shared__ float s_c[256];
  __shared__ float s_red[8][64];
  __shared__ float s_part[4][64];
  const int tid = threadIdx.x, lane = tid & 31, warp = tid >> 5;
  const int slab = blockIdx.x >> 2, kr = blockIdx.x & 3;
  const int rg = tid >> 3, ch = tid & 7;
  uint4 w[8];
  const bf16* wp = wmod + (size_t)(kr * 256 + rg) * (6 * DM) + slab * 64 + ch * 8;
#pragma unroll
  for (int i = 0; i < 8; i++) w[i] = __ldg(reinterpret_cast<const uint4*>(wp + (size_t)i * 32 * (6 * DM)));
  {
    float cv = __bfloat162float(c[kr * 256 + tid]);
    float sv = cv / (1.0f + __expf(-cv));
    s_c[tid] = round_bf16(sv);
  }
  if (blockIdx.x < 128) {
#pragma unroll
    for (int r = 0; r < 2; r++) {
      const int row = blockIdx.x * 16 + warp * 2 + r;
      const uint4* xp = reinterpret_cast<const uint4*>(x + (size_t)row * DM);
      uint4 v[4];
#pragma unroll
      for (int i = 0; i < 4; i++) v[i] = __ldg(xp + lane + i * 32);
      float f[32];
#pragma unroll
      for (int i = 0; i < 4; i++) {
        f[i * 8 + 0] = bf16_lo(v[i].x); f[i * 8 + 1] = bf16_hi(v[i].x);
        f[i * 8 + 2] = bf16_lo(v[i].y); f[i * 8 + 3] = bf16_hi(v[i].y);
        f[i * 8 + 4] = bf16_lo(v[i].z); f[i * 8 + 5] = bf16_hi(v[i].z);
        f[i * 8 + 6] = bf16_lo(v[i].w); f[i * 8 + 7] = bf16_hi(v[i].w);
      }
      float s = 0.f;
#pragma unroll
      for (int i = 0; i < 32; i++) s += f[i];
#pragma unroll
      for (int o = 16; o > 0; o >>= 1) s += __shfl_xor_sync(0xffffffffu, s, o);
      const float mean = s * (1.0f / DM);
      float q = 0.f;
#pragma unroll
      for (int i = 0; i < 32; i++) { float d = f[i] - mean; q += d * d; }
#pragma unroll
      for (int o = 16; o > 0; o >>= 1) q += __shfl_xor_sync(0xffffffffu, q, o);
      if (lane == 0) g_stats1[row] = make_float2(mean, rsqrtf(q * (1.0f / DM) + 1e-5f));
    }
  }
  __syncthreads();
  float acc[8];
#pragma unroll
  for (int j = 0; j < 8; j++) acc[j] = 0.f;
#pragma unroll
  for (int i = 0; i < 8; i++) {
    const float cv = s_c[rg + i * 32];
    acc[0] += cv * bf16_lo(w[i].x); acc[1] += cv * bf16_hi(w[i].x);
    acc[2] += cv * bf16_lo(w[i].y); acc[3] += cv * bf16_hi(w[i].y);
    acc[4] += cv * bf16_lo(w[i].z); acc[5] += cv * bf16_hi(w[i].z);
    acc[6] += cv * bf16_lo(w[i].w); acc[7] += cv * bf16_hi(w[i].w);
  }
#pragma unroll
  for (int j = 0; j < 8; j++) {
    acc[j] += __shfl_xor_sync(0xffffffffu, acc[j], 8);
    acc[j] += __shfl_xor_sync(0xffffffffu, acc[j], 16);
  }
  if (lane < 8) {
#pragma unroll
    for (int j = 0; j < 8; j++) s_red[warp][lane * 8 + j] = acc[j];
  }
  __syncthreads();
  if (tid < 64) {
    float s = 0.f;
#pragma unroll
    for (int wv = 0; wv < 8; wv++) s += s_red[wv][tid];
    uint32_t la = smem_u32(&s_part[kr][tid]), ra;
    asm volatile("mapa.shared::cluster.u32 %0, %1, %2;" : "=r"(ra) : "r"(la), "r"(0));
    asm volatile("st.shared::cluster.f32 [%0], %1;" ::"r"(ra), "f"(s) : "memory");
  }
  cluster_sync_all();
  if (kr == 0 && tid < 64) {
    float s = (s_part[0][tid] + s_part[1][tid]) + (s_part[2][tid] + s_part[3][tid]);
    g_mod[slab * 64 + tid] = round_bf16(s);
  }
}

template <int WHICH>
__global__ void __launch_bounds__(256) ln_kernel(const bf16* __restrict__ xin) {
  const int lane = threadIdx.x & 31, warp = threadIdx.x >> 5;
  const int row = blockIdx.x * 8 + warp;
  const bf16* src = WHICH == 0 ? xin : g_x1;
  float mean, rstd;
  if (WHICH == 0) {
    float2 st = g_stats1[row];
    mean = st.x; rstd = st.y;
  } else {
    float s = 0.f;
#pragma unroll
    for (int j = 0; j < 8; j++) s += g_stats2[row * 8 + j].x;
    mean = s * (1.0f / DM);
    float m2 = 0.f;
#pragma unroll
    for (int j = 0; j < 8; j++) {
      float2 p = g_stats2[row * 8 + j];
      float d = p.x * (1.0f / 128) - mean;
      m2 += p.y + 128.f * d * d;
    }
    rstd = rsqrtf(m2 * (1.0f / DM) + 1e-5f);
  }
  const float* sh = g_mod + (WHICH == 0 ? 0 : 3 * DM);
  const float* sc = g_mod + (WHICH == 0 ? DM : 4 * DM);
  const uint4* xp = reinterpret_cast<const uint4*>(src + (size_t)row * DM);
  uint4* hp = reinterpret_cast<uint4*>(g_h + (size_t)row * DM);
#pragma unroll
  for (int i = 0; i < 4; i++) {
    uint4 v = xp[lane + i * 32];
    const int c0 = (lane + i * 32) * 8;
    uint32_t in[4] = {v.x, v.y, v.z, v.w}, o[4];
#pragma unroll
    for (int j = 0; j < 4; j++) {
      float a = (bf16_lo(in[j]) - mean) * rstd, b = (bf16_hi(in[j]) - mean) * rstd;
      a = a * (1.0f + sc[c0 + 2 * j]) + sh[c0 + 2 * j];
      b = b * (1.0f + sc[c0 + 2 * j + 1]) + sh[c0 + 2 * j + 1];
      o[j] = pack_bf16(a, b);
    }
    hp[lane + i * 32] = make_uint4(o[0], o[1], o[2], o[3]);
  }
}

enum { EPI_QKV = 0, EPI_OPROJ = 1, EPI_FFN1 = 2, EPI_FFN2 = 3 };

template <int BN_, int AW_, int STAGES_, int CM_, int CN_, int EPI_, int KTOT_, int NTILES_>
struct GemmCfg {
  static constexpr int BN = BN_, AW = AW_, STAGES = STAGES_, CM = CM_, CN = CN_, EPI = EPI_, KTOT = KTOT_, NTILES = NTILES_;
  static constexpr int KS = 64 / CM;
  static constexpr int A_BYTES = 128 * 64 * 2;
  static constexpr int B_BYTES = BN * 64 * 2;
  static constexpr int B2_BYTES = (EPI == EPI_QKV) ? 1024 : 0;
  static constexpr int STAGE_BYTES = A_BYTES + B_BYTES + B2_BYTES;
  static constexpr int SMEM = STAGES * STAGE_BYTES + 1024 + 256;
  static constexpr int SWZ_B = (AW == 64) ? 1 : 2;
};

struct EpiParams {
  const bf16* x;
  bf16* out;
};

template <class C>
__global__ void __launch_bounds__(384, 1)
    gemm_kernel(const __grid_constant__ CUtensorMap tmA, const __grid_constant__ CUtensorMap tmB,
                const __grid_constant__ CUtensorMap tmB2k, const __grid_constant__ CUtensorMap tmB2v, EpiParams ep) {
  constexpr int BN = C::BN, AW = C::AW, STAGES = C::STAGES, CM = C::CM, CN = C::CN, EPI = C::EPI, KS = C::KS;
  constexpr int NKB = C::KTOT / 64;
  constexpr int NPEER = CM + CN - 1;
  extern __shared__ uint8_t smem_raw[];
  const uint32_t smem_base = (smem_u32(smem_raw) + 1023) & ~1023u;
  const uint32_t bar_base = smem_base + STAGES * C::STAGE_BYTES;
  auto full_bar = [&](int s) { return bar_base + s * 8; };
  auto empty_bar = [&](int s) { return bar_base + (STAGES + s) * 8; };
  const int tid = threadIdx.x, warp = tid >> 5, lane = tid & 31, wg = tid >> 7;
  const int cx = blockIdx.x % CN, cy = blockIdx.y % CM;
  const int m0 = blockIdx.y * 128;

  if (tid == 0) {
    prefetch_tmap(&tmA);
    prefetch_tmap(&tmB);
    for (int s = 0; s < STAGES; s++) {
      mbar_init(full_bar(s), 1);
      mbar_init(empty_bar(s), 8 * NPEER);
    }
    fence_barrier_init();
  }
  if (CM * CN > 1) cluster_sync_all(); else __syncthreads();
  pdl_launch();

  if (wg == 0) {
    reg_dealloc<40>();
    if (warp == 0 && lane == 0) {
      pdl_wait();
      uint16_t maskA = 0, maskB = 0;
      for (int i = 0; i < CN; i++) maskA |= (uint16_t)(1u << (cy * CN + i));
      for (int i = 0; i < CM; i++) maskB |= (uint16_t)(1u << (i * CN + cx));
      int stage = 0;
      uint32_t phase = 1;
      for (int t = 0; t < C::NTILES; t++) {
        const int nt = blockIdx.x + t * gridDim.x;
        for (int kb = 0; kb < NKB; kb++) {
          if (CM * CN > 1) mbar_wait_cluster(empty_bar(stage), phase); else mbar_wait(empty_bar(stage), phase);
          const uint32_t sa = smem_base + stage * C::STAGE_BYTES;
          const uint32_t sb = sa + C::A_BYTES;
          mbar_expect_tx(full_bar(stage), C::STAGE_BYTES);
          if (CN > 1)
            tma_2d_mc(sa + cx * (128 / CN) * 128, &tmA, full_bar(stage), kb * 64, m0 + cx * (128 / CN), maskA);
          else
            tma_2d(sa, &tmA, full_bar(stage), kb * 64, m0);
          if (CM > 1)
            tma_3d_mc(sb + cy * (BN * KS * 2), &tmB, full_bar(stage), 0, kb * 64 + cy * KS, nt * (BN / AW), maskB);
          else
            tma_3d(sb, &tmB, full_bar(stage), 0, kb * 64, nt * (BN / AW));
          if (EPI == EPI_QKV) {
            const uint32_t sb2 = sb + C::B_BYTES;
            if (nt < 4) tma_2d(sb2, &tmB2k, full_bar(stage), nt * 8, kb * 64);
            else tma_2d(sb2, &tmB2v, full_bar(stage), (nt - 4) * 8, kb * 64);
          }
          if (++stage == STAGES) { stage = 0; phase ^= 1; }
        }
      }
    }
  } else {
    reg_alloc<232>();
    const int cw = wg - 1;
    uint32_t peer = 0;
    if (lane < CN) peer = cy * CN + lane;
    else if (lane < NPEER) {
      int j = lane - CN;
      if (j >= cy) j++;
      peer = j * CN + cx;
    }
    pdl_wait();
    int stage = 0;
    uint32_t phase = 0;
    for (int t = 0; t < C::NTILES; t++) {
      const int nt = blockIdx.x + t * gridDim.x;
      const int n0 = nt * BN;
      float acc[BN / 2];
      float acc2[4];
#pragma unroll
      for (int i = 0; i < BN / 2; i++) acc[i] = 0.f;
#pragma unroll
      for (int i = 0; i < 4; i++) acc2[i] = 0.f;
      int prev_stage = -1;
      for (int kb = 0; kb < NKB; kb++) {
        mbar_wait(full_bar(stage), phase);
        const uint32_t sa = smem_base + stage * C::STAGE_BYTES + cw * 64 * 128;
        const uint32_t sb = smem_base + stage * C::STAGE_BYTES + C::A_BYTES;
        wgmma_fence();
#pragma unroll
        for (int kk = 0; kk < 4; kk++) {
          const uint64_t da = make_desc(sa + kk * 32, 16, 1024, 1);
          const int slice = (kk * 16) / KS, r0 = (kk * 16) % KS;
          const uint64_t db = make_desc(sb + slice * (BN * KS * 2) + r0 * (AW * 2), KS * AW * 2, 8 * AW * 2, C::SWZ_B);
          WG<BN>::ss(acc, da, db, 1);
          if (EPI == EPI_QKV) {
            const uint64_t db2 = make_desc(sb + C::B_BYTES + kk * 256, 128, 128, 0);
            wgmma_ss_n8_t1(acc2, da, db2, 1);
          }
        }
        wgmma_commit();
        if (prev_stage >= 0) {
          wgmma_wait<1>();
          if (CM * CN > 1) { if (lane < NPEER) mbar_arrive_cluster(empty_bar(prev_stage), peer); }
          else if (lane == 0) mbar_arrive(empty_bar(prev_stage));
        }
        prev_stage = stage;
        if (++stage == STAGES) { stage = 0; phase ^= 1; }
      }
      wgmma_wait<0>();
      if (CM * CN > 1) { if (lane < NPEER) mbar_arrive_cluster(empty_bar(prev_stage), peer); }
      else if (lane == 0) mbar_arrive(empty_bar(prev_stage));
      fence_regs(acc);
      fence_regs(acc2);

      const int r0 = m0 + cw * 64 + (warp & 3) * 16 + (lane >> 2);
      const int r1 = r0 + 8;
      const int cq = (lane & 3) * 2;
      if (EPI == EPI_QKV) {
#pragma unroll
        for (int j = 0; j < BN / 8; j++) {
          const int col = n0 + j * 8 + cq;
          *reinterpret_cast<uint32_t*>(g_q + (size_t)r0 * DM + col) = pack_bf16(acc[j * 4 + 0], acc[j * 4 + 1]);
          *reinterpret_cast<uint32_t*>(g_q + (size_t)r1 * DM + col) = pack_bf16(acc[j * 4 + 2], acc[j * 4 + 3]);
        }
        if (nt < 4) {
          const int col = nt * 8 + cq;
          *reinterpret_cast<uint32_t*>(g_k + (size_t)r0 * DH + col) = pack_bf16(acc2[0], acc2[1]);
          *reinterpret_cast<uint32_t*>(g_k + (size_t)r1 * DH + col) = pack_bf16(acc2[2], acc2[3]);
        } else {
          const int col = (nt - 4) * 8 + cq;
          g_vt[(size_t)col * SEQ + r0] = __float2bfloat16_rn(acc2[0]);
          g_vt[(size_t)(col + 1) * SEQ + r0] = __float2bfloat16_rn(acc2[1]);
          g_vt[(size_t)col * SEQ + r1] = __float2bfloat16_rn(acc2[2]);
          g_vt[(size_t)(col + 1) * SEQ + r1] = __float2bfloat16_rn(acc2[3]);
        }
      } else if (EPI == EPI_OPROJ || EPI == EPI_FFN2) {
        const float* gate = g_mod + (EPI == EPI_OPROJ ? 2 * DM : 5 * DM);
        const bf16* res = EPI == EPI_OPROJ ? ep.x : g_x1;
        bf16* dst = EPI == EPI_OPROJ ? g_x1 : ep.out;
        float s0 = 0.f, s1 = 0.f;
#pragma unroll
        for (int j = 0; j < BN / 8; j++) {
          const int col = n0 + j * 8 + cq;
          const float2 g = *reinterpret_cast<const float2*>(gate + col);
          const uint32_t xa = *reinterpret_cast<const uint32_t*>(res + (size_t)r0 * DM + col);
          const uint32_t xb = *reinterpret_cast<const uint32_t*>(res + (size_t)r1 * DM + col);
          float v0 = bf16_lo(xa) + round_bf16(g.x * round_bf16(acc[j * 4 + 0]));
          float v1 = bf16_hi(xa) + round_bf16(g.y * round_bf16(acc[j * 4 + 1]));
          float v2 = bf16_lo(xb) + round_bf16(g.x * round_bf16(acc[j * 4 + 2]));
          float v3 = bf16_hi(xb) + round_bf16(g.y * round_bf16(acc[j * 4 + 3]));
          const uint32_t pa = pack_bf16(v0, v1), pb = pack_bf16(v2, v3);
          *reinterpret_cast<uint32_t*>(dst + (size_t)r0 * DM + col) = pa;
          *reinterpret_cast<uint32_t*>(dst + (size_t)r1 * DM + col) = pb;
          if (EPI == EPI_OPROJ) {
            acc[j * 4 + 0] = bf16_lo(pa); acc[j * 4 + 1] = bf16_hi(pa);
            acc[j * 4 + 2] = bf16_lo(pb); acc[j * 4 + 3] = bf16_hi(pb);
            s0 += acc[j * 4 + 0] + acc[j * 4 + 1];
            s1 += acc[j * 4 + 2] + acc[j * 4 + 3];
          }
        }
        if (EPI == EPI_OPROJ) {
          s0 += __shfl_xor_sync(0xffffffffu, s0, 1); s0 += __shfl_xor_sync(0xffffffffu, s0, 2);
          s1 += __shfl_xor_sync(0xffffffffu, s1, 1); s1 += __shfl_xor_sync(0xffffffffu, s1, 2);
          const float mu0 = s0 * (1.0f / 128), mu1 = s1 * (1.0f / 128);
          float q0 = 0.f, q1 = 0.f;
#pragma unroll
          for (int j = 0; j < BN / 8; j++) {
            float d;
            d = acc[j * 4 + 0] - mu0; q0 += d * d;
            d = acc[j * 4 + 1] - mu0; q0 += d * d;
            d = acc[j * 4 + 2] - mu1; q1 += d * d;
            d = acc[j * 4 + 3] - mu1; q1 += d * d;
          }
          q0 += __shfl_xor_sync(0xffffffffu, q0, 1); q0 += __shfl_xor_sync(0xffffffffu, q0, 2);
          q1 += __shfl_xor_sync(0xffffffffu, q1, 1); q1 += __shfl_xor_sync(0xffffffffu, q1, 2);
          if ((lane & 3) == 0) {
            g_stats2[r0 * 8 + nt] = make_float2(s0, q0);
            g_stats2[r1 * 8 + nt] = make_float2(s1, q1);
          }
        }
      } else {
#pragma unroll
        for (int j = 0; j < BN / 8; j++) {
          const int col = n0 + j * 8 + cq;
          *reinterpret_cast<uint32_t*>(g_hff + (size_t)r0 * DFF + col) =
              pack_bf16(fmaxf(acc[j * 4 + 0], 0.f), fmaxf(acc[j * 4 + 1], 0.f));
          *reinterpret_cast<uint32_t*>(g_hff + (size_t)r1 * DFF + col) =
              pack_bf16(fmaxf(acc[j * 4 + 2], 0.f), fmaxf(acc[j * 4 + 3], 0.f));
        }
      }
    }
  }
  if (CM * CN > 1) cluster_sync_all();
}

constexpr int AT_STAGES = 8;
constexpr int AT_KBYTES = 128 * 64;
constexpr int AT_VBYTES = 2 * 5 * 1024;
constexpr int AT_STAGE_BYTES = AT_KBYTES + AT_VBYTES;
constexpr int AT_QBYTES = 512 * 64;
constexpr int AT_SMEM = AT_QBYTES + AT_STAGES * AT_STAGE_BYTES + 1024 + 256;
constexpr float SOFTMAX_C = 0.17677669529663687f * 1.4426950408889634f;
#define POLY_DEG 3
#define POLY_NUM 3

__device__ __noinline__ void attn_slow_row(int row, int cq, float* o8) {
  float q[32];
  for (int d = 0; d < 32; d++) q[d] = __bfloat162float(g_q[(size_t)row * 32 + d]);
  float m = -INFINITY, l = 0.f, o[8];
  for (int j = 0; j < 8; j++) o[j] = 0.f;
  for (int key = 0; key < SEQ; key++) {
    float s = 0.f;
    for (int d = 0; d < 32; d++) s += q[d] * __bfloat162float(g_k[key * 32 + d]);
    s *= SOFTMAX_C;
    const float mn = fmaxf(m, s);
    const float sc = exp2f(m - mn), p = exp2f(s - mn);
    m = mn;
    l = l * sc + p;
    for (int j = 0; j < 4; j++) {
      o[2 * j] = o[2 * j] * sc + p * __bfloat162float(g_vt[(j * 8 + cq) * SEQ + key]);
      o[2 * j + 1] = o[2 * j + 1] * sc + p * __bfloat162float(g_vt[(j * 8 + cq + 1) * SEQ + key]);
    }
  }
  for (int j = 0; j < 8; j++) o8[j] = o[j] / l;
}

__device__ __forceinline__ float exp2_poly(float s, float ub) {
  constexpr float MAGIC = 12582912.f - 125.f;
  const float u = __saturatef(fmaf(s, SOFTMAX_C / 252.f, ub));
  const float t = fmaf(u, 252.f, MAGIC);
  const float nf = t - MAGIC;
  const float f = fmaf(u, 252.f, -nf);
  float p = fmaf(f, 5.517166906e-02f, 2.426111222e-01f);
  p = fmaf(p, f, 6.932609855e-01f);
  p = fmaf(p, f, 9.999280735e-01f);
  return __uint_as_float(__float_as_uint(p) + (__float_as_uint(t) << 23));
}

__global__ void __launch_bounds__(512, 1)
    attn_kernel(const __grid_constant__ CUtensorMap tmQ, const __grid_constant__ CUtensorMap tmK,
                const __grid_constant__ CUtensorMap tmV) {
  extern __shared__ uint8_t smem_raw[];
  const uint32_t smem_base = (smem_u32(smem_raw) + 1023) & ~1023u;
  const uint32_t sq = smem_base;
  const uint32_t skv = smem_base + AT_QBYTES;
  const uint32_t bar_base = skv + AT_STAGES * AT_STAGE_BYTES;
  auto full_bar = [&](int s) { return bar_base + s * 8; };
  auto empty_bar = [&](int s) { return bar_base + (AT_STAGES + s) * 8; };
  const uint32_t q_bar = bar_base + 2 * AT_STAGES * 8;
  const int tid = threadIdx.x, warp = tid >> 5, lane = tid & 31, wg = tid >> 7;

  if (tid == 0) {
    prefetch_tmap(&tmQ); prefetch_tmap(&tmK); prefetch_tmap(&tmV);
    for (int s = 0; s < AT_STAGES; s++) {
      mbar_init(full_bar(s), 1);
      mbar_init(empty_bar(s), 16);
    }
    mbar_init(q_bar, 1);
    fence_barrier_init();
  }
  for (int i = tid; i < AT_STAGES * 2 * 64; i += 512) {
    const int blk = i >> 6, e = i & 63;
    const uint32_t a = skv + (blk >> 1) * AT_STAGE_BYTES + AT_KBYTES + (blk & 1) * 5120 + 4096 + e * 16;
    asm volatile("st.shared.v4.b32 [%0], {%1, %1, %1, %1};" ::"r"(a), "r"(0x3F803F80u) : "memory");
  }
  fence_proxy_async();
  __syncthreads();
  pdl_launch();

  auto load_kv = [&](int kt) {
    const int st = kt % AT_STAGES;
    const uint32_t sk = skv + st * AT_STAGE_BYTES;
    mbar_expect_tx(full_bar(st), AT_KBYTES + 2 * 4096);
    tma_2d(sk, &tmK, full_bar(st), 0, kt * 128);
    tma_2d(sk + AT_KBYTES, &tmV, full_bar(st), kt * 128, 0);
    tma_2d(sk + AT_KBYTES + 5120, &tmV, full_bar(st), kt * 128 + 64, 0);
  };
  if (tid == 0) {
    pdl_wait();
    mbar_expect_tx(q_bar, AT_QBYTES);
    tma_2d(sq, &tmQ, q_bar, 0, blockIdx.x * 512);
    tma_2d(sq + 256 * 64, &tmQ, q_bar, 0, blockIdx.x * 512 + 256);
    for (int kt = 0; kt < AT_STAGES; kt++) load_kv(kt);
  }
  __syncwarp();
  {
    float o[2][20];
    float mref[2][2];
    bool bad[2][2];
#pragma unroll
    for (int t = 0; t < 2; t++) {
#pragma unroll
      for (int i = 0; i < 20; i++) o[t][i] = 0.f;
      mref[t][0] = mref[t][1] = 0.f;
      bad[t][0] = bad[t][1] = false;
    }
    mbar_wait(q_bar, 0);
    int stage = 0;
    uint32_t phase = 0;
    for (int kt = 0; kt < SEQ / 128; kt++) {
      if (tid == 0 && kt >= AT_STAGES / 2 && kt + AT_STAGES / 2 < SEQ / 128) {
        mbar_wait(empty_bar((kt + AT_STAGES / 2) % AT_STAGES), 0);
        load_kv(kt + AT_STAGES / 2);
      }
      __syncwarp();
      mbar_wait(full_bar(stage), phase);
      const uint32_t sk = skv + stage * AT_STAGE_BYTES;
#pragma unroll
      for (int half = 0; half < 2; half++) {
#pragma unroll
        for (int t = 0; t < 2; t++) {
          float s[32];
          const uint32_t qa = sq + (wg * 128 + t * 64) * 64;
          const uint32_t ka = sk + half * 64 * 64;
          wgmma_fence();
          wgmma_ss_z_n64_t0(s, make_desc(qa, 16, 512, 2), make_desc(ka, 16, 512, 2));
          wgmma_ss_n64_t0(s, make_desc(qa + 32, 16, 512, 2), make_desc(ka + 32, 16, 512, 2), 1);
          wgmma_commit();
          wgmma_wait<0>();
          fence_regs(s);
          fence_regs(o[t]);
          if (kt == 0 && half == 0) {
            float m0 = s[0], m1 = s[2];
#pragma unroll
            for (int j = 0; j < 8; j++) {
              m0 = fmaxf(m0, fmaxf(s[j * 4 + 0], s[j * 4 + 1]));
              m1 = fmaxf(m1, fmaxf(s[j * 4 + 2], s[j * 4 + 3]));
            }
            m0 = fmaxf(m0, __shfl_xor_sync(0xffffffffu, m0, 1)); m0 = fmaxf(m0, __shfl_xor_sync(0xffffffffu, m0, 2));
            m1 = fmaxf(m1, __shfl_xor_sync(0xffffffffu, m1, 1)); m1 = fmaxf(m1, __shfl_xor_sync(0xffffffffu, m1, 2));
            mref[t][0] = m0 * SOFTMAX_C;
            mref[t][1] = m1 * SOFTMAX_C;
          } else if (!(fmaxf(o[t][16], o[t][18]) < 65536.f)) {
#pragma unroll
            for (int h = 0; h < 2; h++) {
              const float l = o[t][16 + 2 * h];
              if (!(l < 1.329228e36f)) { bad[t][h] = true; }
              else if (l >= 65536.f) {
                const int e = (int)(__float_as_uint(l) >> 23) - 127;
                const float sc = __uint_as_float((uint32_t)(127 - e) << 23);
                mref[t][h] += (float)e;
#pragma unroll
                for (int j = 0; j < 5; j++) { o[t][j * 4 + 2 * h] *= sc; o[t][j * 4 + 2 * h + 1] *= sc; }
              }
            }
          }
          const float nm0 = -mref[t][0], nm1 = -mref[t][1];
          const float ub0 = (125.f - mref[t][0]) * (1.0f / 252.f), ub1 = (125.f - mref[t][1]) * (1.0f / 252.f);
          uint32_t p[16];
#pragma unroll
          for (int j = 0; j < 8; j++) {
            float e[4];
#pragma unroll
            for (int i = 0; i < 4; i++) {
              const int idx = j * 4 + i;
              const bool usepoly = ((idx * 5) & 7) < POLY_NUM;
              if (usepoly) e[i] = exp2_poly(s[idx], (i & 2) ? ub1 : ub0);
              else e[i] = ex2(fmaf(s[idx], SOFTMAX_C, (i & 2) ? nm1 : nm0));
            }
            p[j * 2 + 0] = pack_bf16(e[0], e[1]);
            p[j * 2 + 1] = pack_bf16(e[2], e[3]);
          }
          const uint32_t va = sk + AT_KBYTES + half * 5120;
          wgmma_fence();
#pragma unroll
          for (int kk = 0; kk < 4; kk++)
            wgmma_rs_n40_t0(o[t], p[kk * 4 + 0], p[kk * 4 + 1], p[kk * 4 + 2], p[kk * 4 + 3],
                            make_desc(va + kk * 32, 16, 1024, 1), 1);
          wgmma_commit();
        }
      }
      wgmma_wait<0>();
      if (lane == 0) mbar_arrive(empty_bar(stage));
      if (++stage == AT_STAGES) { stage = 0; phase ^= 1; }
    }
    fence_regs(o[0]);
    fence_regs(o[1]);
    const int cq = (lane & 3) * 2;
#pragma unroll
    for (int t = 0; t < 2; t++) {
#pragma unroll
      for (int h = 0; h < 2; h++) {
        const int row = blockIdx.x * 512 + wg * 128 + t * 64 + (warp & 3) * 16 + (lane >> 2) + h * 8;
        const float l = o[t][16 + 2 * h];
        float r[8];
        if (bad[t][h] || !(l < 1.329228e36f) || !(l > 0.f)) {
          attn_slow_row(row, cq, r);
        } else {
          const float inv = 1.0f / l;
#pragma unroll
          for (int j = 0; j < 4; j++) { r[2 * j] = o[t][j * 4 + 2 * h] * inv; r[2 * j + 1] = o[t][j * 4 + 2 * h + 1] * inv; }
        }
#pragma unroll
        for (int j = 0; j < 4; j++)
          *reinterpret_cast<uint32_t*>(g_o + (size_t)row * 32 + j * 8 + cq) = pack_bf16(r[2 * j], r[2 * j + 1]);
      }
    }
  }
}

typedef CUresult (*EncodeFn)(CUtensorMap*, CUtensorMapDataType, cuuint32_t, void*, const cuuint64_t*, const cuuint64_t*,
                             const cuuint32_t*, const cuuint32_t*, CUtensorMapInterleave, CUtensorMapSwizzle,
                             CUtensorMapL2promotion, CUtensorMapFloatOOBfill);

EncodeFn g_encode = nullptr;

CUtensorMap make_map(const void* ptr, int rank, const cuuint64_t* dims, const cuuint64_t* strides, const cuuint32_t* box,
                     CUtensorMapSwizzle swz) {
  CUtensorMap m;
  cuuint32_t es[3] = {1, 1, 1};
  g_encode(&m, CU_TENSOR_MAP_DATA_TYPE_BFLOAT16, rank, const_cast<void*>(ptr), dims, strides, box, es,
           CU_TENSOR_MAP_INTERLEAVE_NONE, swz, CU_TENSOR_MAP_L2_PROMOTION_L2_256B, CU_TENSOR_MAP_FLOAT_OOB_FILL_NONE);
  return m;
}
CUtensorMap map2d(const void* ptr, int rows, int cols, int br, int bc, CUtensorMapSwizzle swz) {
  cuuint64_t dims[2] = {(cuuint64_t)cols, (cuuint64_t)rows};
  cuuint64_t strides[1] = {(cuuint64_t)cols * 2};
  cuuint32_t box[2] = {(cuuint32_t)bc, (cuuint32_t)br};
  return make_map(ptr, 2, dims, strides, box, swz);
}
CUtensorMap mapB(const void* ptr, int K, int N, int AW, int ks, int BN) {
  cuuint64_t dims[3] = {(cuuint64_t)AW, (cuuint64_t)K, (cuuint64_t)(N / AW)};
  cuuint64_t strides[2] = {(cuuint64_t)N * 2, (cuuint64_t)AW * 2};
  cuuint32_t box[3] = {(cuuint32_t)AW, (cuuint32_t)ks, (cuuint32_t)(BN / AW)};
  return make_map(ptr, 3, dims, strides, box, AW == 64 ? CU_TENSOR_MAP_SWIZZLE_128B : CU_TENSOR_MAP_SWIZZLE_64B);
}

template <class K, class... Args>
void launch(K kern, dim3 grid, dim3 block, int smem, dim3 cluster, bool pdl, Args... args) {
  cudaLaunchConfig_t cfg = {};
  cfg.gridDim = grid;
  cfg.blockDim = block;
  cfg.dynamicSmemBytes = smem;
  cfg.stream = cudaStreamPerThread;
  cudaLaunchAttribute at[2];
  int n = 0;
  if (cluster.x * cluster.y * cluster.z > 1) {
    at[n].id = cudaLaunchAttributeClusterDimension;
    at[n].val.clusterDim.x = cluster.x; at[n].val.clusterDim.y = cluster.y; at[n].val.clusterDim.z = cluster.z;
    n++;
  }
  if (pdl) {
    at[n].id = cudaLaunchAttributeProgrammaticStreamSerialization;
    at[n].val.programmaticStreamSerializationAllowed = 1;
    n++;
  }
  cfg.attrs = at;
  cfg.numAttrs = n;
  cudaLaunchKernelEx(&cfg, kern, args...);
}

#define CFG_QKV 128, 64, 5, 2, 2
#define CFG_OP 128, 64, 6, 2, 2
#define CFG_F1 224, 32, 4, 2, 2
#define CFG_F2 128, 64, 6, 2, 2
typedef GemmCfg<CFG_QKV, EPI_QKV, DM, 1> CfgQKV;
typedef GemmCfg<CFG_OP, EPI_OPROJ, DM, 1> CfgOP;
typedef GemmCfg<CFG_F1, EPI_FFN1, DM, 2> CfgF1;
typedef GemmCfg<CFG_F2, EPI_FFN2, DFF, 1> CfgF2;

struct Maps {
  CUtensorMap h_a, wq_b, wk_b, wv_b, q_in, k_in, v_in, o_a, wo_b, h2_a, w1_b, hff_a, w2_b;
  const void* key[10];
  bool valid;
};
Maps g_maps;

}

extern "C" void kernel_launch(void* const* d_in, const int* in_sizes, int n_in, void* d_out, int out_size) {
  const bf16* x = (const bf16*)d_in[0];
  const bf16* wq = (const bf16*)d_in[1];
  const bf16* wk = (const bf16*)d_in[2];
  const bf16* wv = (const bf16*)d_in[3];
  const bf16* wo = (const bf16*)d_in[4];
  const bf16* w1 = (const bf16*)d_in[6];
  const bf16* w2 = (const bf16*)d_in[7];
  const bf16* c = (const bf16*)d_in[8];
  const bf16* wmod = (const bf16*)d_in[9];
  bf16* out = (bf16*)d_out;

  bool same = g_maps.valid;
  for (int i = 0; i < 10 && same; i++) same = g_maps.key[i] == d_in[i];
  if (!same) {
    if (!g_encode) {
      cudaDriverEntryPointQueryResult qr;
      void* fn = nullptr;
      cudaGetDriverEntryPoint("cuTensorMapEncodeTiled", &fn, cudaEnableDefault, &qr);
      g_encode = (EncodeFn)fn;
    }
    void *ph, *pq, *pk, *pvt, *po, *phff;
    cudaGetSymbolAddress(&ph, g_h);
    cudaGetSymbolAddress(&pq, g_q);
    cudaGetSymbolAddress(&pk, g_k);
    cudaGetSymbolAddress(&pvt, g_vt);
    cudaGetSymbolAddress(&po, g_o);
    cudaGetSymbolAddress(&phff, g_hff);
    g_maps.h_a = map2d(ph, SEQ, DM, 128 / CfgQKV::CN, 64, CU_TENSOR_MAP_SWIZZLE_128B);
    g_maps.wq_b = mapB(wq, DM, DM, CfgQKV::AW, CfgQKV::KS, CfgQKV::BN);
    g_maps.wk_b = map2d(wk, DM, DH, 64, 8, CU_TENSOR_MAP_SWIZZLE_NONE);
    g_maps.wv_b = map2d(wv, DM, DH, 64, 8, CU_TENSOR_MAP_SWIZZLE_NONE);
    g_maps.q_in = map2d(pq, SEQ * 32, DH, 256, 32, CU_TENSOR_MAP_SWIZZLE_64B);
    g_maps.k_in = map2d(pk, SEQ, DH, 128, 32, CU_TENSOR_MAP_SWIZZLE_64B);
    g_maps.v_in = map2d(pvt, DH, SEQ, 32, 64, CU_TENSOR_MAP_SWIZZLE_128B);
    g_maps.o_a = map2d(po, SEQ, DM, 128 / CfgOP::CN, 64, CU_TENSOR_MAP_SWIZZLE_128B);
    g_maps.wo_b = mapB(wo, DM, DM, CfgOP::AW, CfgOP::KS, CfgOP::BN);
    g_maps.h2_a = map2d(ph, SEQ, DM, 128 / CfgF1::CN, 64, CU_TENSOR_MAP_SWIZZLE_128B);
    g_maps.w1_b = mapB(w1, DM, DFF, CfgF1::AW, CfgF1::KS, CfgF1::BN);
    g_maps.hff_a = map2d(phff, SEQ, DFF, 128 / CfgF2::CN, 64, CU_TENSOR_MAP_SWIZZLE_128B);
    g_maps.w2_b = mapB(w2, DFF, DM, CfgF2::AW, CfgF2::KS, CfgF2::BN);
    for (int i = 0; i < 10; i++) g_maps.key[i] = d_in[i];
    g_maps.valid = true;
    cudaFuncSetAttribute(gemm_kernel<CfgQKV>, cudaFuncAttributeMaxDynamicSharedMemorySize, CfgQKV::SMEM);
    cudaFuncSetAttribute(gemm_kernel<CfgOP>, cudaFuncAttributeMaxDynamicSharedMemorySize, CfgOP::SMEM);
    cudaFuncSetAttribute(gemm_kernel<CfgF1>, cudaFuncAttributeMaxDynamicSharedMemorySize, CfgF1::SMEM);
    cudaFuncSetAttribute(gemm_kernel<CfgF2>, cudaFuncAttributeMaxDynamicSharedMemorySize, CfgF2::SMEM);
    cudaFuncSetAttribute(attn_kernel, cudaFuncAttributeMaxDynamicSharedMemorySize, AT_SMEM);
  }
  EpiParams ep{x, out};
  const dim3 one(1, 1, 1);
  mod_kernel<<<384, 256, 0, cudaStreamPerThread>>>(c, wmod, x);
  ln_kernel<0><<<256, 256, 0, cudaStreamPerThread>>>(x);
  launch(gemm_kernel<CfgQKV>, dim3(8, 16), dim3(384), CfgQKV::SMEM, dim3(CfgQKV::CN, CfgQKV::CM, 1), false, g_maps.h_a,
         g_maps.wq_b, g_maps.wk_b, g_maps.wv_b, ep);
  launch(attn_kernel, dim3(128), dim3(512), AT_SMEM, one, false, g_maps.q_in, g_maps.k_in, g_maps.v_in);
  launch(gemm_kernel<CfgOP>, dim3(8, 16), dim3(384), CfgOP::SMEM, dim3(CfgOP::CN, CfgOP::CM, 1), false, g_maps.o_a,
         g_maps.wo_b, g_maps.wk_b, g_maps.wv_b, ep);
  ln_kernel<1><<<256, 256, 0, cudaStreamPerThread>>>(x);
  launch(gemm_kernel<CfgF1>, dim3(8, 16), dim3(384), CfgF1::SMEM, dim3(CfgF1::CN, CfgF1::CM, 1), false, g_maps.h2_a,
         g_maps.w1_b, g_maps.wk_b, g_maps.wv_b, ep);
  launch(gemm_kernel<CfgF2>, dim3(8, 16), dim3(384), CfgF2::SMEM, dim3(CfgF2::CN, CfgF2::CM, 1), false, g_maps.hff_a,
         g_maps.w2_b, g_maps.wk_b, g_maps.wv_b, ep);
}
```

```cpp
#include <cuda_runtime.h>
#include <cuda_bf16.h>
#include <cuda.h>
#include <stdint.h>

namespace {

constexpr int SEQ = 2048, DM = 1024, DH = 32, DFF = 3584;
typedef __nv_bfloat16 bf16;
constexpr float K_SCALE = 9.5367431640625e-07f;

__device__ __align__(1024) uint32_t g_part[8][2 * DM];
__device__ __align__(1024) float g_mod2[4 * DM];
__device__ __align__(1024) bf16 g_h[SEQ * DM];
__device__ __align__(1024) bf16 g_q[SEQ * DM];
__device__ __align__(1024) bf16 g_k[SEQ * DH];
__device__ __align__(1024) bf16 g_vt[DH * SEQ];
__device__ __align__(1024) bf16 g_o[SEQ * DM];
__device__ __align__(1024) bf16 g_x1[SEQ * DM];
__device__ __align__(1024) float2 g_stats2[SEQ * 8];
__device__ __align__(1024) bf16 g_hff[SEQ * DFF];

#define TSTAMP(k, i) do {} while (0)
#define CSTAMP(i) do {} while (0)
__device__ __forceinline__ uint32_t smem_u32(const void* p) { return (uint32_t)__cvta_generic_to_shared(p); }

__device__ __forceinline__ void mbar_init(uint32_t bar, uint32_t count) {
  asm volatile("mbarrier.init.shared::cta.b64 [%0], %1;" ::"r"(bar), "r"(count) : "memory");
}
__device__ __forceinline__ void mbar_expect_tx(uint32_t bar, uint32_t bytes) {
  asm volatile("mbarrier.arrive.expect_tx.shared::cta.b64 _, [%0], %1;" ::"r"(bar), "r"(bytes) : "memory");
}
__device__ __forceinline__ void mbar_arrive(uint32_t bar) {
  asm volatile("mbarrier.arrive.shared::cta.b64 _, [%0];" ::"r"(bar) : "memory");
}
__device__ __forceinline__ void mbar_arrive_cluster(uint32_t bar, uint32_t cta) {
  asm volatile(
      "{\n.reg .b32 ra;\n"
      "mapa.shared::cluster.u32 ra, %0, %1;\n"
      "mbarrier.arrive.shared::cluster.b64 _, [ra];\n}\n" ::"r"(bar), "r"(cta)
      : "memory");
}
__device__ __forceinline__ bool mbar_try_wait(uint32_t bar, uint32_t parity) {
  uint32_t ok;
  asm volatile(
      "{\n.reg .pred p;\n"
      "mbarrier.try_wait.parity.shared::cta.b64 p, [%1], %2;\n"
      "selp.u32 %0, 1, 0, p;\n}\n"
      : "=r"(ok)
      : "r"(bar), "r"(parity)
      : "memory");
  return ok != 0;
}
__device__ __forceinline__ void mbar_wait(uint32_t bar, uint32_t parity) {
  uint32_t spins = 0;
  while (!mbar_try_wait(bar, parity)) {
    if (++spins > (1u << 24)) __trap();
  }
}
__device__ __forceinline__ void mbar_wait_cluster(uint32_t bar, uint32_t parity) {
  uint32_t spins = 0;
  while (true) {
    uint32_t ok;
    asm volatile(
        "{\n.reg .pred p;\n"
        "mbarrier.try_wait.parity.acquire.cluster.shared::cta.b64 p, [%1], %2;\n"
        "selp.u32 %0, 1, 0, p;\n}\n"
        : "=r"(ok)
        : "r"(bar), "r"(parity)
        : "memory");
    if (ok) break;
    if (++spins > (1u << 24)) __trap();
  }
}
__device__ __forceinline__ void fence_barrier_init() { asm volatile("fence.mbarrier_init.release.cluster;" ::: "memory"); }
__device__ __forceinline__ void fence_proxy_async() { asm volatile("fence.proxy.async.shared::cta;" ::: "memory"); }
__device__ __forceinline__ void cluster_sync_all() {
  asm volatile("barrier.cluster.arrive.release.aligned;\nbarrier.cluster.wait.acquire.aligned;" ::: "memory");
}
__device__ __forceinline__ void pdl_wait() { asm volatile("griddepcontrol.wait;" ::: "memory"); }
__device__ __forceinline__ void pdl_launch() { asm volatile("griddepcontrol.launch_dependents;" ::: "memory"); }
__device__ __forceinline__ void prefetch_tmap(const CUtensorMap* m) {
  asm volatile("prefetch.tensormap [%0];" ::"l"(reinterpret_cast<uint64_t>(m)) : "memory");
}
__device__ __forceinline__ void tma_2d(uint32_t dst, const CUtensorMap* m, uint32_t bar, int c0, int c1) {
  asm volatile(
      "cp.async.bulk.tensor.2d.shared::cluster.global.mbarrier::complete_tx::bytes [%0], [%1, {%3, %4}], [%2];" ::"r"(dst),
      "l"(reinterpret_cast<uint64_t>(m)), "r"(bar), "r"(c0), "r"(c1)
      : "memory");
}
__device__ __forceinline__ void tma_2d_mc(uint32_t dst, const CUtensorMap* m, uint32_t bar, int c0, int c1, uint16_t mask) {
  asm volatile(
      "cp.async.bulk.tensor.2d.shared::cluster.global.mbarrier::complete_tx::bytes.multicast::cluster [%0], [%1, {%3, %4}], "
      "[%2], %5;" ::"r"(dst),
      "l"(reinterpret_cast<uint64_t>(m)), "r"(bar), "r"(c0), "r"(c1), "h"(mask)
      : "memory");
}
__device__ __forceinline__ void tma_3d(uint32_t dst, const CUtensorMap* m, uint32_t bar, int c0, int c1, int c2) {
  asm volatile(
      "cp.async.bulk.tensor.3d.shared::cluster.global.mbarrier::complete_tx::bytes [%0], [%1, {%3, %4, %5}], [%2];" ::"r"(dst),
      "l"(reinterpret_cast<uint64_t>(m)), "r"(bar), "r"(c0), "r"(c1), "r"(c2)
      : "memory");
}
__device__ __forceinline__ void tma_3d_mc(uint32_t dst, const CUtensorMap* m, uint32_t bar, int c0, int c1, int c2,
                                          uint16_t mask) {
  asm volatile(
      "cp.async.bulk.tensor.3d.shared::cluster.global.mbarrier::complete_tx::bytes.multicast::cluster [%0], [%1, {%3, %4, "
      "%5}], [%2], %6;" ::"r"(dst),
      "l"(reinterpret_cast<uint64_t>(m)), "r"(bar), "r"(c0), "r"(c1), "r"(c2), "h"(mask)
      : "memory");
}
__device__ __forceinline__ void tma_5d(uint32_t dst, const CUtensorMap* m, uint32_t bar, int c0, int c4) {
  asm volatile(
      "cp.async.bulk.tensor.5d.shared::cluster.global.mbarrier::complete_tx::bytes [%0], [%1, {%3, %5, %5, %5, %4}], [%2];" ::"r"(dst),
      "l"(reinterpret_cast<uint64_t>(m)), "r"(bar), "r"(c0), "r"(c4), "r"(0)
      : "memory");
}
__device__ __forceinline__ void tma_store_2d(const CUtensorMap* m, uint32_t src, int c0, int c1) {
  asm volatile("cp.async.bulk.tensor.2d.global.shared::cta.bulk_group [%0, {%2, %3}], [%1];" ::"l"(reinterpret_cast<uint64_t>(m)),
               "r"(src), "r"(c0), "r"(c1)
               : "memory");
}
__device__ __forceinline__ void l2_prefetch(const void* p, uint32_t bytes) {
  asm volatile("cp.async.bulk.prefetch.L2.global [%0], %1;" ::"l"(p), "r"(bytes) : "memory");
}
__device__ __forceinline__ void bulk_load(uint32_t dst, const void* src, uint32_t bytes, uint32_t bar) {
  asm volatile("cp.async.bulk.shared::cluster.global.mbarrier::complete_tx::bytes [%0], [%1], %2, [%3];" ::"r"(dst), "l"(src),
               "r"(bytes), "r"(bar)
               : "memory");
}
__device__ __forceinline__ int qk_idx(int row, int e) { return row * 32 + ((((e >> 3) ^ (row >> 1)) & 3) << 3) + (e & 7); }
__device__ __forceinline__ int vt_idx(int d, int key) {
  return (key >> 6) * 2048 + d * 64 + ((((key >> 3) ^ d) & 7) << 3) + (key & 7);
}
__device__ __forceinline__ void bulk_commit() { asm volatile("cp.async.bulk.commit_group;" ::: "memory"); }
__device__ __forceinline__ void bulk_wait_all() { asm volatile("cp.async.bulk.wait_group.read 0;" ::: "memory"); }
__device__ __forceinline__ void ldsm_x4(uint32_t (&r)[4], uint32_t a) {
  asm volatile("ldmatrix.sync.aligned.m8n8.x4.shared.b16 {%0, %1, %2, %3}, [%4];" : "=r"(r[0]), "=r"(r[1]), "=r"(r[2]), "=r"(r[3]) : "r"(a) : "memory");
}
__device__ __forceinline__ void stsm_x4(uint32_t a, const uint32_t (&r)[4]) {
  asm volatile("stmatrix.sync.aligned.m8n8.x4.shared.b16 [%0], {%1, %2, %3, %4};" ::"r"(a), "r"(r[0]), "r"(r[1]), "r"(r[2]), "r"(r[3]) : "memory");
}
__device__ __forceinline__ void nbar_sync(int id, int n) { asm volatile("bar.sync %0, %1;" ::"r"(id), "r"(n) : "memory"); }
__device__ __forceinline__ void wgmma_fence() { asm volatile("wgmma.fence.sync.aligned;" ::: "memory"); }
__device__ __forceinline__ void wgmma_commit() { asm volatile("wgmma.commit_group.sync.aligned;" ::: "memory"); }
template <int N>
__device__ __forceinline__ void wgmma_wait() {
  asm volatile("wgmma.wait_group.sync.aligned %0;" ::"n"(N) : "memory");
}
template <int R>
__device__ __forceinline__ void reg_alloc() { asm volatile("setmaxnreg.inc.sync.aligned.u32 %0;" ::"n"(R)); }
template <int R>
__device__ __forceinline__ void reg_dealloc() { asm volatile("setmaxnreg.dec.sync.aligned.u32 %0;" ::"n"(R)); }

template <int N>
__device__ __forceinline__ void fence_regs(float (&d)[N]) {
#pragma unroll
  for (int i = 0; i < N; i++) asm volatile("" : "+f"(d[i])::"memory");
}

__device__ __forceinline__ uint64_t make_desc(uint32_t addr, uint32_t lbo, uint32_t sbo, uint32_t swz) {
  return (uint64_t)((addr & 0x3FFFF) >> 4) | ((uint64_t)((lbo & 0x3FFFF) >> 4) << 16) |
         ((uint64_t)((sbo & 0x3FFFF) >> 4) << 32) | ((uint64_t)swz << 62);
}
__device__ __forceinline__ uint32_t pack_bf16(float lo, float hi) {
  uint32_t r;
  asm("cvt.rn.bf16x2.f32 %0, %1, %2;" : "=r"(r) : "f"(hi), "f"(lo));
  return r;
}
__device__ __forceinline__ float bf16_lo(uint32_t v) { return __uint_as_float(v << 16); }
__device__ __forceinline__ float bf16_hi(uint32_t v) { return __uint_as_float(v & 0xFFFF0000u); }
__device__ __forceinline__ float round_bf16(float x) { return __bfloat162float(__float2bfloat16_rn(x)); }
__device__ __forceinline__ float ex2(float x) {
  float y;
  asm("ex2.approx.ftz.f32 %0, %1;" : "=f"(y) : "f"(x));
  return y;
}

__device__ __forceinline__ void wgmma_ss_n128_t1(float (&d)[64], uint64_t da, uint64_t db, int sd) {
  asm volatile("{\n.reg .pred p;\nsetp.ne.b32 p, %66, 0;\n"
    "wgmma.mma_async.sync.aligned.m64n128k16.f32.bf16.bf16 {%0, %1, %2, %3, %4, %5, %6, %7, %8, %9, %10, %11, %12, %13, %14, %15, %16, %17, %18, %19, %20, %21, %22, %23, %24, %25, %26, %27, %28, %29, %30, %31, %32, %33, %34, %35, %36, %37, %38, %39, %40, %41, %42, %43, %44, %45, %46, %47, %48, %49, %50, %51, %52, %53, %54, %55, %56, %57, %58, %59, %60, %61, %62, %63}, %64, %65, p, 1, 1, 0, 1;\n}\n"
    : "+f"(d[0]), "+f"(d[1]), "+f"(d[2]), "+f"(d[3]), "+f"(d[4]), "+f"(d[5]), "+f"(d[6]), "+f"(d[7]), "+f"(d[8]), "+f"(d[9]), "+f"(d[10]), "+f"(d[11]), "+f"(d[12]), "+f"(d[13]), "+f"(d[14]), "+f"(d[15]), "+f"(d[16]), "+f"(d[17]), "+f"(d[18]), "+f"(d[19]), "+f"(d[20]), "+f"(d[21]), "+f"(d[22]), "+f"(d[23]), "+f"(d[24]), "+f"(d[25]), "+f"(d[26]), "+f"(d[27]), "+f"(d[28]), "+f"(d[29]), "+f"(d[30]), "+f"(d[31]), "+f"(d[32]), "+f"(d[33]), "+f"(d[34]), "+f"(d[35]), "+f"(d[36]), "+f"(d[37]), "+f"(d[38]), "+f"(d[39]), "+f"(d[40]), "+f"(d[41]), "+f"(d[42]), "+f"(d[43]), "+f"(d[44]), "+f"(d[45]), "+f"(d[46]), "+f"(d[47]), "+f"(d[48]), "+f"(d[49]), "+f"(d[50]), "+f"(d[51]), "+f"(d[52]), "+f"(d[53]), "+f"(d[54]), "+f"(d[55]), "+f"(d[56]), "+f"(d[57]), "+f"(d[58]), "+f"(d[59]), "+f"(d[60]), "+f"(d[61]), "+f"(d[62]), "+f"(d[63])
    : "l"(da), "l"(db), "r"(sd));
}

__device__ __forceinline__ void wgmma_ss_n136_t1(float (&d)[68], uint64_t da, uint64_t db, int sd) {
  asm volatile("{\n.reg .pred p;\nsetp.ne.b32 p, %70, 0;\n"
    "wgmma.mma_async.sync.aligned.m64n136k16.f32.bf16.bf16 {%0, %1, %2, %3, %4, %5, %6, %7, %8, %9, %10, %11, %12, %13, %14, %15, %16, %17, %18, %19, %20, %21, %22, %23, %24, %25, %26, %27, %28, %29, %30, %31, %32, %33, %34, %35, %36, %37, %38, %39, %40, %41, %42, %43, %44, %45, %46, %47, %48, %49, %50, %51, %52, %53, %54, %55, %56, %57, %58, %59, %60, %61, %62, %63, %64, %65, %66, %67}, %68, %69, p, 1, 1, 0, 1;\n}\n"
    : "+f"(d[0]), "+f"(d[1]), "+f"(d[2]), "+f"(d[3]), "+f"(d[4]), "+f"(d[5]), "+f"(d[6]), "+f"(d[7]), "+f"(d[8]), "+f"(d[9]), "+f"(d[10]), "+f"(d[11]), "+f"(d[12]), "+f"(d[13]), "+f"(d[14]), "+f"(d[15]), "+f"(d[16]), "+f"(d[17]), "+f"(d[18]), "+f"(d[19]), "+f"(d[20]), "+f"(d[21]), "+f"(d[22]), "+f"(d[23]), "+f"(d[24]), "+f"(d[25]), "+f"(d[26]), "+f"(d[27]), "+f"(d[28]), "+f"(d[29]), "+f"(d[30]), "+f"(d[31]), "+f"(d[32]), "+f"(d[33]), "+f"(d[34]), "+f"(d[35]), "+f"(d[36]), "+f"(d[37]), "+f"(d[38]), "+f"(d[39]), "+f"(d[40]), "+f"(d[41]), "+f"(d[42]), "+f"(d[43]), "+f"(d[44]), "+f"(d[45]), "+f"(d[46]), "+f"(d[47]), "+f"(d[48]), "+f"(d[49]), "+f"(d[50]), "+f"(d[51]), "+f"(d[52]), "+f"(d[53]), "+f"(d[54]), "+f"(d[55]), "+f"(d[56]), "+f"(d[57]), "+f"(d[58]), "+f"(d[59]), "+f"(d[60]), "+f"(d[61]), "+f"(d[62]), "+f"(d[63]), "+f"(d[64]), "+f"(d[65]), "+f"(d[66]), "+f"(d[67])
    : "l"(da), "l"(db), "r"(sd));
}

__device__ __forceinline__ void wgmma_ss_n192_t1(float (&d)[96], uint64_t da, uint64_t db, int sd) {
  asm volatile("{\n.reg .pred p;\nsetp.ne.b32 p, %98, 0;\n"
    "wgmma.mma_async.sync.aligned.m64n192k16.f32.bf16.bf16 {%0, %1, %2, %3, %4, %5, %6, %7, %8, %9, %10, %11, %12, %13, %14, %15, %16, %17, %18, %19, %20, %21, %22, %23, %24, %25, %26, %27, %28, %29, %30, %31, %32, %33, %34, %35, %36, %37, %38, %39, %40, %41, %42, %43, %44, %45, %46, %47, %48, %49, %50, %51, %52, %53, %54, %55, %56, %57, %58, %59, %60, %61, %62, %63, %64, %65, %66, %67, %68, %69, %70, %71, %72, %73, %74, %75, %76, %77, %78, %79, %80, %81, %82, %83, %84, %85, %86, %87, %88, %89, %90, %91, %92, %93, %94, %95}, %96, %97, p, 1, 1, 0, 1;\n}\n"
    : "+f"(d[0]), "+f"(d[1]), "+f"(d[2]), "+f"(d[3]), "+f"(d[4]), "+f"(d[5]), "+f"(d[6]), "+f"(d[7]), "+f"(d[8]), "+f"(d[9]), "+f"(d[10]), "+f"(d[11]), "+f"(d[12]), "+f"(d[13]), "+f"(d[14]), "+f"(d[15]), "+f"(d[16]), "+f"(d[17]), "+f"(d[18]), "+f"(d[19]), "+f"(d[20]), "+f"(d[21]), "+f"(d[22]), "+f"(d[23]), "+f"(d[24]), "+f"(d[25]), "+f"(d[26]), "+f"(d[27]), "+f"(d[28]), "+f"(d[29]), "+f"(d[30]), "+f"(d[31]), "+f"(d[32]), "+f"(d[33]), "+f"(d[34]), "+f"(d[35]), "+f"(d[36]), "+f"(d[37]), "+f"(d[38]), "+f"(d[39]), "+f"(d[40]), "+f"(d[41]), "+f"(d[42]), "+f"(d[43]), "+f"(d[44]), "+f"(d[45]), "+f"(d[46]), "+f"(d[47]), "+f"(d[48]), "+f"(d[49]), "+f"(d[50]), "+f"(d[51]), "+f"(d[52]), "+f"(d[53]), "+f"(d[54]), "+f"(d[55]), "+f"(d[56]), "+f"(d[57]), "+f"(d[58]), "+f"(d[59]), "+f"(d[60]), "+f"(d[61]), "+f"(d[62]), "+f"(d[63]), "+f"(d[64]), "+f"(d[65]), "+f"(d[66]), "+f"(d[67]), "+f"(d[68]), "+f"(d[69]), "+f"(d[70]), "+f"(d[71]), "+f"(d[72]), "+f"(d[73]), "+f"(d[74]), "+f"(d[75]), "+f"(d[76]), "+f"(d[77]), "+f"(d[78]), "+f"(d[79]), "+f"(d[80]), "+f"(d[81]), "+f"(d[82]), "+f"(d[83]), "+f"(d[84]), "+f"(d[85]), "+f"(d[86]), "+f"(d[87]), "+f"(d[88]), "+f"(d[89]), "+f"(d[90]), "+f"(d[91]), "+f"(d[92]), "+f"(d[93]), "+f"(d[94]), "+f"(d[95])
    : "l"(da), "l"(db), "r"(sd));
}

__device__ __forceinline__ void wgmma_ss_n256_t1(float (&d)[128], uint64_t da, uint64_t db, int sd) {
  asm volatile("{\n.reg .pred p;\nsetp.ne.b32 p, %130, 0;\n"
    "wgmma.mma_async.sync.aligned.m64n256k16.f32.bf16.bf16 {%0, %1, %2, %3, %4, %5, %6, %7, %8, %9, %10, %11, %12, %13, %14, %15, %16, %17, %18, %19, %20, %21, %22, %23, %24, %25, %26, %27, %28, %29, %30, %31, %32, %33, %34, %35, %36, %37, %38, %39, %40, %41, %42, %43, %44, %45, %46, %47, %48, %49, %50, %51, %52, %53, %54, %55, %56, %57, %58, %59, %60, %61, %62, %63, %64, %65, %66, %67, %68, %69, %70, %71, %72, %73, %74, %75, %76, %77, %78, %79, %80, %81, %82, %83, %84, %85, %86, %87, %88, %89, %90, %91, %92, %93, %94, %95, %96, %97, %98, %99, %100, %101, %102, %103, %104, %105, %106, %107, %108, %109, %110, %111, %112, %113, %114, %115, %116, %117, %118, %119, %120, %121, %122, %123, %124, %125, %126, %127}, %128, %129, p, 1, 1, 0, 1;\n}\n"
    : "+f"(d[0]), "+f"(d[1]), "+f"(d[2]), "+f"(d[3]), "+f"(d[4]), "+f"(d[5]), "+f"(d[6]), "+f"(d[7]), "+f"(d[8]), "+f"(d[9]), "+f"(d[10]), "+f"(d[11]), "+f"(d[12]), "+f"(d[13]), "+f"(d[14]), "+f"(d[15]), "+f"(d[16]), "+f"(d[17]), "+f"(d[18]), "+f"(d[19]), "+f"(d[20]), "+f"(d[21]), "+f"(d[22]), "+f"(d[23]), "+f"(d[24]), "+f"(d[25]), "+f"(d[26]), "+f"(d[27]), "+f"(d[28]), "+f"(d[29]), "+f"(d[30]), "+f"(d[31]), "+f"(d[32]), "+f"(d[33]), "+f"(d[34]), "+f"(d[35]), "+f"(d[36]), "+f"(d[37]), "+f"(d[38]), "+f"(d[39]), "+f"(d[40]), "+f"(d[41]), "+f"(d[42]), "+f"(d[43]), "+f"(d[44]), "+f"(d[45]), "+f"(d[46]), "+f"(d[47]), "+f"(d[48]), "+f"(d[49]), "+f"(d[50]), "+f"(d[51]), "+f"(d[52]), "+f"(d[53]), "+f"(d[54]), "+f"(d[55]), "+f"(d[56]), "+f"(d[57]), "+f"(d[58]), "+f"(d[59]), "+f"(d[60]), "+f"(d[61]), "+f"(d[62]), "+f"(d[63]), "+f"(d[64]), "+f"(d[65]), "+f"(d[66]), "+f"(d[67]), "+f"(d[68]), "+f"(d[69]), "+f"(d[70]), "+f"(d[71]), "+f"(d[72]), "+f"(d[73]), "+f"(d[74]), "+f"(d[75]), "+f"(d[76]), "+f"(d[77]), "+f"(d[78]), "+f"(d[79]), "+f"(d[80]), "+f"(d[81]), "+f"(d[82]), "+f"(d[83]), "+f"(d[84]), "+f"(d[85]), "+f"(d[86]), "+f"(d[87]), "+f"(d[88]), "+f"(d[89]), "+f"(d[90]), "+f"(d[91]), "+f"(d[92]), "+f"(d[93]), "+f"(d[94]), "+f"(d[95]), "+f"(d[96]), "+f"(d[97]), "+f"(d[98]), "+f"(d[99]), "+f"(d[100]), "+f"(d[101]), "+f"(d[102]), "+f"(d[103]), "+f"(d[104]), "+f"(d[105]), "+f"(d[106]), "+f"(d[107]), "+f"(d[108]), "+f"(d[109]), "+f"(d[110]), "+f"(d[111]), "+f"(d[112]), "+f"(d[113]), "+f"(d[114]), "+f"(d[115]), "+f"(d[116]), "+f"(d[117]), "+f"(d[118]), "+f"(d[119]), "+f"(d[120]), "+f"(d[121]), "+f"(d[122]), "+f"(d[123]), "+f"(d[124]), "+f"(d[125]), "+f"(d[126]), "+f"(d[127])
    : "l"(da), "l"(db), "r"(sd));
}

__device__ __forceinline__ void wgmma_ss_n64_t0(float (&d)[32], uint64_t da, uint64_t db, int sd) {
  asm volatile("{\n.reg .pred p;\nsetp.ne.b32 p, %34, 0;\n"
    "wgmma.mma_async.sync.aligned.m64n64k16.f32.bf16.bf16 {%0, %1, %2, %3, %4, %5, %6, %7, %8, %9, %10, %11, %12, %13, %14, %15, %16, %17, %18, %19, %20, %21, %22, %23, %24, %25, %26, %27, %28, %29, %30, %31}, %32, %33, p, 1, 1, 0, 0;\n}\n"
    : "+f"(d[0]), "+f"(d[1]), "+f"(d[2]), "+f"(d[3]), "+f"(d[4]), "+f"(d[5]), "+f"(d[6]), "+f"(d[7]), "+f"(d[8]), "+f"(d[9]), "+f"(d[10]), "+f"(d[11]), "+f"(d[12]), "+f"(d[13]), "+f"(d[14]), "+f"(d[15]), "+f"(d[16]), "+f"(d[17]), "+f"(d[18]), "+f"(d[19]), "+f"(d[20]), "+f"(d[21]), "+f"(d[22]), "+f"(d[23]), "+f"(d[24]), "+f"(d[25]), "+f"(d[26]), "+f"(d[27]), "+f"(d[28]), "+f"(d[29]), "+f"(d[30]), "+f"(d[31])
    : "l"(da), "l"(db), "r"(sd));
}

__device__ __forceinline__ void wgmma_ss_z_n64_t0(float (&d)[32], uint64_t da, uint64_t db) {
  asm volatile("{\n.reg .pred p;\nsetp.ne.b32 p, 0, 0;\n"
    "wgmma.mma_async.sync.aligned.m64n64k16.f32.bf16.bf16 {%0, %1, %2, %3, %4, %5, %6, %7, %8, %9, %10, %11, %12, %13, %14, %15, %16, %17, %18, %19, %20, %21, %22, %23, %24, %25, %26, %27, %28, %29, %30, %31}, %32, %33, p, 1, 1, 0, 0;\n}\n"
    : "=f"(d[0]), "=f"(d[1]), "=f"(d[2]), "=f"(d[3]), "=f"(d[4]), "=f"(d[5]), "=f"(d[6]), "=f"(d[7]), "=f"(d[8]), "=f"(d[9]), "=f"(d[10]), "=f"(d[11]), "=f"(d[12]), "=f"(d[13]), "=f"(d[14]), "=f"(d[15]), "=f"(d[16]), "=f"(d[17]), "=f"(d[18]), "=f"(d[19]), "=f"(d[20]), "=f"(d[21]), "=f"(d[22]), "=f"(d[23]), "=f"(d[24]), "=f"(d[25]), "=f"(d[26]), "=f"(d[27]), "=f"(d[28]), "=f"(d[29]), "=f"(d[30]), "=f"(d[31])
    : "l"(da), "l"(db));
}

__device__ __forceinline__ void wgmma_rs_n40_t0(float (&d)[20], uint32_t a0, uint32_t a1, uint32_t a2, uint32_t a3, uint64_t db, int sd) {
  asm volatile("{\n.reg .pred p;\nsetp.ne.b32 p, %25, 0;\n"
    "wgmma.mma_async.sync.aligned.m64n40k16.f32.bf16.bf16 {%0, %1, %2, %3, %4, %5, %6, %7, %8, %9, %10, %11, %12, %13, %14, %15, %16, %17, %18, %19}, {%20, %21, %22, %23}, %24, p, 1, 1, 0;\n}\n"
    : "+f"(d[0]), "+f"(d[1]), "+f"(d[2]), "+f"(d[3]), "+f"(d[4]), "+f"(d[5]), "+f"(d[6]), "+f"(d[7]), "+f"(d[8]), "+f"(d[9]), "+f"(d[10]), "+f"(d[11]), "+f"(d[12]), "+f"(d[13]), "+f"(d[14]), "+f"(d[15]), "+f"(d[16]), "+f"(d[17]), "+f"(d[18]), "+f"(d[19])
    : "r"(a0), "r"(a1), "r"(a2), "r"(a3), "l"(db), "r"(sd));
}

template <int N>
struct WG;
template <>
struct WG<128> {
  static __device__ __forceinline__ void ss(float (&d)[64], uint64_t a, uint64_t b, int sd) { wgmma_ss_n128_t1(d, a, b, sd); }
};
template <>
struct WG<136> {
  static __device__ __forceinline__ void ss(float (&d)[68], uint64_t a, uint64_t b, int sd) { wgmma_ss_n136_t1(d, a, b, sd); }
};
template <>
struct WG<192> {
  static __device__ __forceinline__ void ss(float (&d)[96], uint64_t a, uint64_t b, int sd) { wgmma_ss_n192_t1(d, a, b, sd); }
};
template <>
struct WG<256> {
  static __device__ __forceinline__ void ss(float (&d)[128], uint64_t a, uint64_t b, int sd) { wgmma_ss_n256_t1(d, a, b, sd); }
};

__device__ __forceinline__ uint4 ld_volatile_v4(const void* p) {
  uint4 v;
  asm volatile("ld.volatile.global.v4.u32 {%0, %1, %2, %3}, [%4];" : "=r"(v.x), "=r"(v.y), "=r"(v.z), "=r"(v.w) : "l"(p) : "memory");
  return v;
}
__device__ __forceinline__ void fma8(float (&acc)[8], float cv, const uint4& q) {
  acc[0] += cv * bf16_lo(q.x); acc[1] += cv * bf16_hi(q.x);
  acc[2] += cv * bf16_lo(q.y); acc[3] += cv * bf16_hi(q.y);
  acc[4] += cv * bf16_lo(q.z); acc[5] += cv * bf16_hi(q.z);
  acc[6] += cv * bf16_lo(q.w); acc[7] += cv * bf16_hi(q.w);
}
__device__ __forceinline__ float silu_bf16(bf16 c) {
  const float cv = __bfloat162float(c);
  return round_bf16(cv / (1.0f + __expf(-cv)));
}

__global__ void __launch_bounds__(512, 1)
    pre_kernel(const bf16* __restrict__ c, const bf16* __restrict__ wmod, const bf16* __restrict__ x) {
  __shared__ float s_c[128];
  __shared__ float s_red[16][128];
  __shared__ __align__(16) float s_mod[2 * DM];
  const int tid = threadIdx.x, lane = tid & 31, warp = tid >> 5;
  const int slab = blockIdx.x & 15, kr = blockIdx.x >> 4;
  if (tid == 0) TSTAMP(5, 0);
  pdl_launch();
  const int rg = tid >> 4, ch = tid & 15;
  uint4 w[4], v[4];
  const bf16* wp = wmod + (size_t)(kr * 128 + rg) * (6 * DM) + slab * 128 + ch * 8;
#pragma unroll
  for (int i = 0; i < 4; i++) w[i] = __ldg(reinterpret_cast<const uint4*>(wp + (size_t)i * 32 * (6 * DM)));
  const int row = blockIdx.x * 16 + warp;
  const uint4* xp = reinterpret_cast<const uint4*>(x + (size_t)row * DM);
#pragma unroll
  for (int i = 0; i < 4; i++) v[i] = __ldg(xp + lane + i * 32);
  if (tid < 128) {
    s_c[tid] = silu_bf16(c[kr * 128 + tid]);
    g_stats2[blockIdx.x * 128 + tid] = make_float2(0.f, -1.0f);
  }
  __syncthreads();
  {
    float acc[8];
#pragma unroll
    for (int j = 0; j < 8; j++) acc[j] = 0.f;
#pragma unroll
    for (int i = 0; i < 4; i++) fma8(acc, s_c[rg + i * 32], w[i]);
#pragma unroll
    for (int j = 0; j < 8; j++) acc[j] += __shfl_xor_sync(0xffffffffu, acc[j], 16);
    if (lane < 16) {
      *reinterpret_cast<float4*>(&s_red[warp][lane * 8]) = make_float4(acc[0], acc[1], acc[2], acc[3]);
      *reinterpret_cast<float4*>(&s_red[warp][lane * 8 + 4]) = make_float4(acc[4], acc[5], acc[6], acc[7]);
    }
    __syncthreads();
    if (tid < 128) {
      float t = 0.f;
#pragma unroll
      for (int wv = 0; wv < 16; wv++) t += s_red[wv][tid];
      uint32_t u = ~__float_as_uint(t);
      if (u == 0) u = 0x80000000u;
      *reinterpret_cast<volatile uint32_t*>(&g_part[kr][slab * 128 + tid]) = u;
    }
  }
  float f[32];
#pragma unroll
  for (int i = 0; i < 4; i++) {
    f[i * 8 + 0] = bf16_lo(v[i].x); f[i * 8 + 1] = bf16_hi(v[i].x);
    f[i * 8 + 2] = bf16_lo(v[i].y); f[i * 8 + 3] = bf16_hi(v[i].y);
    f[i * 8 + 4] = bf16_lo(v[i].z); f[i * 8 + 5] = bf16_hi(v[i].z);
    f[i * 8 + 6] = bf16_lo(v[i].w); f[i * 8 + 7] = bf16_hi(v[i].w);
  }
  float sum = 0.f;
#pragma unroll
  for (int i = 0; i < 32; i++) sum += f[i];
#pragma unroll
  for (int o = 16; o > 0; o >>= 1) sum += __shfl_xor_sync(0xffffffffu, sum, o);
  const float mean = sum * (1.0f / DM);
  float q = 0.f;
#pragma unroll
  for (int i = 0; i < 32; i++) { f[i] -= mean; q += f[i] * f[i]; }
#pragma unroll
  for (int o = 16; o > 0; o >>= 1) q += __shfl_xor_sync(0xffffffffu, q, o);
  const float rstd = rsqrtf(q * (1.0f / DM) + 1e-5f);
  if (tid == 0) TSTAMP(5, 1);
  {
    uint4 p[8];
    uint32_t spins = 0;
    while (true) {
      bool ok = true;
#pragma unroll
      for (int k = 0; k < 8; k++) p[k] = ld_volatile_v4(&g_part[k][tid * 4]);
#pragma unroll
      for (int k = 0; k < 8; k++) ok = ok && p[k].x != 0 && p[k].y != 0 && p[k].z != 0 && p[k].w != 0;
      if (ok) break;
      if (++spins > (1u << 20)) __trap();
    }
    auto sum8 = [&](auto get) {
      return round_bf16(((get(p[0]) + get(p[1])) + (get(p[2]) + get(p[3]))) + ((get(p[4]) + get(p[5])) + (get(p[6]) + get(p[7]))));
    };
    float4 r;
    r.x = sum8([](const uint4& u) { return __uint_as_float(~u.x); });
    r.y = sum8([](const uint4& u) { return __uint_as_float(~u.y); });
    r.z = sum8([](const uint4& u) { return __uint_as_float(~u.z); });
    r.w = sum8([](const uint4& u) { return __uint_as_float(~u.w); });
    *reinterpret_cast<float4*>(&s_mod[tid * 4]) = r;
  }
  __syncthreads();
  if (tid == 0) TSTAMP(5, 2);
  uint4* hp = reinterpret_cast<uint4*>(g_h + (size_t)row * DM);
#pragma unroll
  for (int i = 0; i < 4; i++) {
    const int c0 = (lane + i * 32) * 8;
    const float4 sa0 = *reinterpret_cast<const float4*>(&s_mod[c0]), sa1 = *reinterpret_cast<const float4*>(&s_mod[c0 + 4]);
    const float4 ca0 = *reinterpret_cast<const float4*>(&s_mod[DM + c0]), ca1 = *reinterpret_cast<const float4*>(&s_mod[DM + c0 + 4]);
    const float* g = f + i * 8;
    hp[lane + i * 32] = make_uint4(pack_bf16(g[0] * rstd * (1.f + ca0.x) + sa0.x, g[1] * rstd * (1.f + ca0.y) + sa0.y),
                                   pack_bf16(g[2] * rstd * (1.f + ca0.z) + sa0.z, g[3] * rstd * (1.f + ca0.w) + sa0.w),
                                   pack_bf16(g[4] * rstd * (1.f + ca1.x) + sa1.x, g[5] * rstd * (1.f + ca1.y) + sa1.y),
                                   pack_bf16(g[6] * rstd * (1.f + ca1.z) + sa1.z, g[7] * rstd * (1.f + ca1.w) + sa1.w));
  }
  if (tid == 0) TSTAMP(5, 3);
}

__device__ __forceinline__ void mod_rest(int sec, const bf16* __restrict__ c, const bf16* __restrict__ wmod, float* sm) {
  const int tid = threadIdx.x;
  float* s_c = sm;
  float* s_red = sm + 1024;
  l2_prefetch(wmod + (size_t)tid * (6 * DM) + (2 + sec) * DM, 2 * DM);
  l2_prefetch(wmod + (size_t)(tid + 512) * (6 * DM) + (2 + sec) * DM, 2 * DM);
  s_c[tid] = silu_bf16(c[tid]);
  s_c[tid + 512] = silu_bf16(c[tid + 512]);
  __syncthreads();
  const int ch = tid & 127, rg = tid >> 7;
  const bf16* wp = wmod + (size_t)(rg * 256) * (6 * DM) + (2 + sec) * DM + ch * 8;
  float acc[8];
#pragma unroll
  for (int j = 0; j < 8; j++) acc[j] = 0.f;
#pragma unroll 1
  for (int r = 0; r < 256; r += 16) {
    uint4 w[16];
#pragma unroll
    for (int i = 0; i < 16; i++) w[i] = __ldg(reinterpret_cast<const uint4*>(wp + (size_t)(r + i) * (6 * DM)));
#pragma unroll
    for (int i = 0; i < 16; i++) fma8(acc, s_c[rg * 256 + r + i], w[i]);
  }
#pragma unroll
  for (int j = 0; j < 8; j++) s_red[rg * 1024 + ch * 8 + j] = acc[j];
  __syncthreads();
#pragma unroll
  for (int i = 0; i < 2; i++) {
    const int col = tid + i * 512;
    g_mod2[sec * DM + col] = round_bf16((s_red[col] + s_red[1024 + col]) + (s_red[2048 + col] + s_red[3072 + col]));
  }
}

enum { EPI_QKV = 0, EPI_OPROJ = 1, EPI_FFN1 = 2, EPI_FFN2 = 3 };

template <int BN_, int BN2_, int STAGES_, int EPI_, int KTOT_>
struct GemmCfg {
  static constexpr int BN = BN_, BN2 = BN2_, STAGES = STAGES_, EPI = EPI_, KTOT = KTOT_, NTILES = BN2_ ? 2 : 1;
  static constexpr int A_BYTES = 128 * 64 * 2;
  static constexpr int B_BYTES = (BN / 64 + (EPI == EPI_QKV ? 1 : 0)) * 8192;
  static constexpr int STAGE_BYTES = A_BYTES + B_BYTES;
  static constexpr bool RES = (EPI == EPI_OPROJ || EPI == EPI_FFN2);
  static constexpr int RES_BYTES = RES ? 128 * BN * 2 : (EPI == EPI_QKV ? DM * 16 : 0);
  static constexpr int SMEM = STAGES * STAGE_BYTES + RES_BYTES + 1024 + 256 + 1536;
};
template <int V>
struct IntC { static constexpr int value = V; };

template <class C>
__global__ void __launch_bounds__(384, 1)
    gemm_kernel(const __grid_constant__ CUtensorMap tmA, const __grid_constant__ CUtensorMap tmB,
                const __grid_constant__ CUtensorMap tmB2k, const __grid_constant__ CUtensorMap tmB2v,
                const __grid_constant__ CUtensorMap tmH, const bf16* __restrict__ wk, const bf16* __restrict__ wv) {
  constexpr int STAGES = C::STAGES, EPI = C::EPI;
  constexpr int NKB = C::KTOT / 64;
  extern __shared__ uint8_t smem_raw[];
  const uint32_t smem_base = (smem_u32(smem_raw) + 1023) & ~1023u;
  const uint32_t s_res = smem_base + STAGES * C::STAGE_BYTES;
  const uint32_t bar_base = s_res + C::RES_BYTES;
  auto full_bar = [&](int s) { return bar_base + s * 8; };
  auto empty_bar = [&](int s) { return bar_base + (STAGES + s) * 8; };
  const uint32_t res_bar = bar_base + 2 * STAGES * 8;
  const uint32_t s_gate = bar_base + 256;
  const int tid = threadIdx.x, warp = tid >> 5, lane = tid & 31, wg = tid >> 7;
  const int m0 = blockIdx.y * 128;
  const int nt = blockIdx.x;
  const int nbase = nt * (C::BN + C::BN2);

  if (tid == 0) {
    TSTAMP(EPI, 0);
    prefetch_tmap(&tmA);
    prefetch_tmap(&tmB);
    for (int s = 0; s < STAGES; s++) {
      mbar_init(full_bar(s), EPI == EPI_QKV ? 2 : 1);
      mbar_init(empty_bar(s), 8);
    }
    mbar_init(res_bar, 1);
    fence_barrier_init();
  }
  __syncthreads();
  pdl_launch();

  if (wg == 0) {
    reg_dealloc<40>();
    if (warp == 0 && lane == 0) {
      auto load_b = [&](int stage, int t, int kb) {
        const uint32_t sb = smem_base + stage * C::STAGE_BYTES + C::A_BYTES;
        const int na = (t ? C::BN2 : C::BN) / 64, n0 = nbase + (t ? C::BN : 0);
        mbar_expect_tx(full_bar(stage), C::A_BYTES + na * 8192);
#pragma unroll 1
        for (int ch = 0; ch < na; ch++) {
          if (EPI == EPI_FFN2) tma_5d(sb + ch * 8192, &tmB, full_bar(stage), n0 + ch * 64, kb * 2);
          else tma_2d(sb + ch * 8192, &tmB, full_bar(stage), n0 + ch * 64, kb * 64);
        }
      };
      auto load_a = [&](int stage, int kb) { tma_2d(smem_base + stage * C::STAGE_BYTES, &tmA, full_bar(stage), kb * 64, m0); };
#pragma unroll 1
      for (int kb = 0; kb < STAGES; kb++) load_b(kb, 0, kb);
      pdl_wait();
      if (EPI != EPI_FFN1) TSTAMP(EPI, 5);
#pragma unroll 1
      for (int kb = 0; kb < STAGES; kb++) load_a(kb, kb);
      if (C::RES) {
        mbar_expect_tx(res_bar, C::RES_BYTES);
#pragma unroll
        for (int q = 0; q < C::BN / 32; q++)
          tma_2d(s_res + q * 8192, &tmB2k, res_bar, nbase + (q >> 1) * 64, m0 + (q & 1) * 64);
      }
      int stage = 0;
      uint32_t phase = 0;
#pragma unroll 1
      for (int it = STAGES; it < C::NTILES * NKB; it++) {
        mbar_wait(empty_bar(stage), phase);
        load_b(stage, it / NKB, it % NKB);
        load_a(stage, it % NKB);
        if (++stage == STAGES) { stage = 0; phase ^= 1; }
      }
    } else if (EPI == EPI_QKV && warp == 1) {
      const bf16* src = (nt < 4 ? wk : wv) + (nt & 3) * 8 + lane * DH;
#pragma unroll 4
      for (int i = 0; i < 32; i++)
        asm volatile("cp.async.cg.shared.global [%0], [%1], 16;" ::"r"(s_res + (i * 32 + lane) * 16), "l"(src + i * 32 * DH) : "memory");
      asm volatile("cp.async.wait_all;" ::: "memory");
      int stage = 0;
      uint32_t phase = 1;
#pragma unroll 1
      for (int kb = 0; kb < NKB; kb++) {
        uint4 v0, v1;
        asm volatile("ld.shared.v4.b32 {%0, %1, %2, %3}, [%4];" : "=r"(v0.x), "=r"(v0.y), "=r"(v0.z), "=r"(v0.w) : "r"(s_res + (kb * 64 + lane) * 16));
        asm volatile("ld.shared.v4.b32 {%0, %1, %2, %3}, [%4];" : "=r"(v1.x), "=r"(v1.y), "=r"(v1.z), "=r"(v1.w) : "r"(s_res + (kb * 64 + 32 + lane) * 16));
        mbar_wait(empty_bar(stage), phase);
        const uint32_t a = smem_base + stage * C::STAGE_BYTES + C::A_BYTES + 2 * 8192 + lane * 128 + ((lane & 7) << 4);
        asm volatile("st.shared.v4.b32 [%0], {%1, %2, %3, %4};" ::"r"(a), "r"(v0.x), "r"(v0.y), "r"(v0.z), "r"(v0.w) : "memory");
        asm volatile("st.shared.v4.b32 [%0], {%1, %2, %3, %4};" ::"r"(a + 4096), "r"(v1.x), "r"(v1.y), "r"(v1.z), "r"(v1.w) : "memory");
        fence_proxy_async();
        __syncwarp();
        if (lane == 0) mbar_arrive(full_bar(stage));
        if (++stage == STAGES) { stage = 0; phase ^= 1; }
      }
    }
  } else {
    reg_alloc<232>();
    const int cw = wg - 1;
    pdl_wait();
    if (EPI == EPI_QKV && tid < 128 + 32)
      reinterpret_cast<uint4*>(&g_part[0][0])[(blockIdx.y * 8 + blockIdx.x) * 32 + tid - 128] = make_uint4(0, 0, 0, 0);
    if (C::RES) {
      const int i = tid - 128, col = nbase + (i & 127);
      if (i < 128) {
        const float g = g_mod2[(EPI == EPI_OPROJ ? 0 : 3 * DM) + col];
        asm volatile("st.shared.b16 [%0], %1;" ::"r"(s_gate + i * 2), "h"((unsigned short)(__float_as_uint(g) >> 16)) : "memory");
      } else if (EPI == EPI_OPROJ) {
        const float sb = g_mod2[DM + col], cb = 1.0f + g_mod2[2 * DM + col];
        asm volatile("st.shared.f32 [%0], %1;" ::"r"(s_gate + i * 4), "f"(sb) : "memory");
        asm volatile("st.shared.f32 [%0], %1;" ::"r"(s_gate + 512 + i * 4), "f"(cb) : "memory");
      }
    }
    int stage = 0;
    uint32_t phase = 0;
    auto tile = [&](auto bn_c, auto t_c) {
      constexpr int BN = decltype(bn_c)::value, t = decltype(t_c)::value;
      constexpr int MN = BN + (EPI == EPI_QKV ? 8 : 0);
      const int n0 = nbase + (t ? C::BN : 0);
      float acc[MN / 2];
#pragma unroll
      for (int i = 0; i < MN / 2; i++) acc[i] = 0.f;
      int prev_stage = -1;
#pragma unroll 1
      for (int kb = 0; kb < NKB; kb++) {
        mbar_wait(full_bar(stage), phase);
        if (tid == 128 && kb == 0) TSTAMP(EPI, 1 + 3 * t);
        const uint32_t sa = smem_base + stage * C::STAGE_BYTES + cw * 64 * 128;
        const uint32_t sb = smem_base + stage * C::STAGE_BYTES + C::A_BYTES;
        wgmma_fence();
#pragma unroll
        for (int kk = 0; kk < 4; kk++)
          WG<MN>::ss(acc, make_desc(sa + kk * 32, 16, 1024, 1), make_desc(sb + kk * 2048, 8192, 1024, 1), 1);
        wgmma_commit();
        if (prev_stage >= 0) {
          wgmma_wait<1>();
          if (lane == 0) mbar_arrive(empty_bar(prev_stage));
        }
        prev_stage = stage;
        if (++stage == STAGES) { stage = 0; phase ^= 1; }
      }
      wgmma_wait<0>();
      if (lane == 0) mbar_arrive(empty_bar(prev_stage));
      fence_regs(acc);
      if (tid == 128) TSTAMP(EPI, 2 + 3 * t);
      const float* acc2 = acc + BN / 2;

      const int r0 = m0 + cw * 64 + (warp & 3) * 16 + (lane >> 2);
      const int r1 = r0 + 8;
      const int cq = (lane & 3) * 2;
      if (EPI == EPI_QKV || EPI == EPI_FFN1) {
        bf16* dst = EPI == EPI_QKV ? g_q : g_hff;
        constexpr int LD = EPI == EPI_QKV ? DM : DFF;
        if (EPI == EPI_FFN1) {
#pragma unroll
          for (int i = 0; i < BN / 2; i++) acc[i] = fmaxf(acc[i], 0.f);
        }
#pragma unroll
        for (int i = 0; i < BN / 32; i++) {
          const float* a = acc + i * 16;
          const int cs = EPI == EPI_QKV ? ((lane ^ (nt * 2 + (i >> 1))) & 3) * 8 : cq * 4;
          *reinterpret_cast<uint4*>(dst + (size_t)r0 * LD + n0 + i * 32 + cs) =
              make_uint4(pack_bf16(a[0], a[1]), pack_bf16(a[4], a[5]), pack_bf16(a[8], a[9]), pack_bf16(a[12], a[13]));
          *reinterpret_cast<uint4*>(dst + (size_t)r1 * LD + n0 + i * 32 + cs) =
              make_uint4(pack_bf16(a[2], a[3]), pack_bf16(a[6], a[7]), pack_bf16(a[10], a[11]), pack_bf16(a[14], a[15]));
        }
        if (EPI == EPI_QKV) {
          if (nt < 4) {
            const int col = cq * 4 + 2 * nt;
            *reinterpret_cast<uint32_t*>(g_k + qk_idx(r0, col)) = pack_bf16(round_bf16(acc2[0]) * K_SCALE, round_bf16(acc2[1]) * K_SCALE);
            *reinterpret_cast<uint32_t*>(g_k + qk_idx(r1, col)) = pack_bf16(round_bf16(acc2[2]) * K_SCALE, round_bf16(acc2[3]) * K_SCALE);
          } else {
            const int col = (cq >> 1) * 8 + 2 * (nt - 4);
            g_vt[vt_idx(col, r0)] = __float2bfloat16_rn(acc2[0]);
            g_vt[vt_idx(col + 1, r0)] = __float2bfloat16_rn(acc2[1]);
            g_vt[vt_idx(col, r1)] = __float2bfloat16_rn(acc2[2]);
            g_vt[vt_idx(col + 1, r1)] = __float2bfloat16_rn(acc2[3]);
          }
        }
      } else {
        nbar_sync(1, 256);
        mbar_wait(res_bar, 0);
        const int lrow = (warp & 3) * 16 + (lane & 7) + ((lane >> 3) & 1) * 8;
        const uint32_t rbase = s_res + cw * 8192 + lrow * 128;
        float s0 = 0.f, s1 = 0.f;
#pragma unroll
        for (int j = 0; j < BN / 8; j += 2) {
          const int cc = j + (lane >> 4);
          const uint32_t addr = rbase + (cc >> 3) * 16384 + (((cc & 7) ^ (lrow & 7)) << 4);
          uint32_t xr[4];
          ldsm_x4(xr, addr);
#pragma unroll
          for (int u = 0; u < 2; u++) {
            uint32_t g;
            asm volatile("ld.shared.b32 %0, [%1];" : "=r"(g) : "r"(s_gate + ((j + u) * 8 + cq) * 2));
            float* a = acc + (j + u) * 4;
            uint32_t pa, pb;
            asm("mul.rn.bf16x2 %0, %1, %2;" : "=r"(pa) : "r"(g), "r"(pack_bf16(a[0], a[1])));
            asm("mul.rn.bf16x2 %0, %1, %2;" : "=r"(pb) : "r"(g), "r"(pack_bf16(a[2], a[3])));
            asm("add.rn.bf16x2 %0, %1, %2;" : "=r"(pa) : "r"(xr[2 * u]), "r"(pa));
            asm("add.rn.bf16x2 %0, %1, %2;" : "=r"(pb) : "r"(xr[2 * u + 1]), "r"(pb));
            xr[2 * u] = pa; xr[2 * u + 1] = pb;
            if (EPI == EPI_OPROJ) {
              a[0] = bf16_lo(pa); a[1] = bf16_hi(pa); a[2] = bf16_lo(pb); a[3] = bf16_hi(pb);
              s0 += a[0] + a[1];
              s1 += a[2] + a[3];
            }
          }
          stsm_x4(addr, xr);
        }
        if (EPI == EPI_OPROJ) {
          s0 += __shfl_xor_sync(0xffffffffu, s0, 1); s0 += __shfl_xor_sync(0xffffffffu, s0, 2);
          s1 += __shfl_xor_sync(0xffffffffu, s1, 1); s1 += __shfl_xor_sync(0xffffffffu, s1, 2);
          const float mu0 = s0 * (1.0f / 128), mu1 = s1 * (1.0f / 128);
          float q0 = 0.f, q1 = 0.f;
#pragma unroll
          for (int j = 0; j < BN / 8; j++) {
            float d;
            d = acc[j * 4 + 0] - mu0; q0 += d * d;
            d = acc[j * 4 + 1] - mu0; q0 += d * d;
            d = acc[j * 4 + 2] - mu1; q1 += d * d;
            d = acc[j * 4 + 3] - mu1; q1 += d * d;
          }
          q0 += __shfl_xor_sync(0xffffffffu, q0, 1); q0 += __shfl_xor_sync(0xffffffffu, q0, 2);
          q1 += __shfl_xor_sync(0xffffffffu, q1, 1); q1 += __shfl_xor_sync(0xffffffffu, q1, 2);
          if ((lane & 3) < 2) {
            const bool h = lane & 1;
            asm volatile("st.volatile.global.v2.f32 [%0], {%1, %2};" ::"l"(&g_stats2[(h ? r1 : r0) * 8 + nt]), "f"(h ? s1 : s0),
                         "f"(h ? q1 : q0)
                         : "memory");
          }
        }
        fence_proxy_async();
        nbar_sync(2 + cw, 128);
        if ((tid & 127) == 0) {
#pragma unroll
          for (int h = 0; h < BN / 64; h++) tma_store_2d(&tmB2v, s_res + h * 16384 + cw * 8192, n0 + h * 64, m0 + cw * 64);
          bulk_commit();
        }
        if (EPI == EPI_OPROJ) {
          float mean[2], rstd[2];
          uint4 pp[2];
          uint32_t spins = 0;
          while (true) {
            pp[0] = ld_volatile_v4(&g_stats2[r0 * 8 + cq]);
            pp[1] = ld_volatile_v4(&g_stats2[r1 * 8 + cq]);
            const bool ok = pp[0].y != 0xBF800000u && pp[0].w != 0xBF800000u && pp[1].y != 0xBF800000u && pp[1].w != 0xBF800000u;
            if (__all_sync(0xffffffffu, ok)) break;
            if (++spins > (1u << 20)) __trap();
          }
          if (tid == 128) TSTAMP(EPI, 4);
#pragma unroll
          for (int h = 0; h < 2; h++) {
            const float4 p = make_float4(__uint_as_float(pp[h].x), __uint_as_float(pp[h].y), __uint_as_float(pp[h].z), __uint_as_float(pp[h].w));
            float sm = p.x + p.z;
            sm += __shfl_xor_sync(0xffffffffu, sm, 1); sm += __shfl_xor_sync(0xffffffffu, sm, 2);
            const float mu = sm * (1.0f / DM);
            const float d0 = p.x * (1.0f / 128) - mu, d1 = p.z * (1.0f / 128) - mu;
            float m2 = p.y + p.w + 128.f * (d0 * d0 + d1 * d1);
            m2 += __shfl_xor_sync(0xffffffffu, m2, 1); m2 += __shfl_xor_sync(0xffffffffu, m2, 2);
            mean[h] = mu;
            rstd[h] = rsqrtf(m2 * (1.0f / DM) + 1e-5f);
          }
          const uint32_t hbase = smem_base + cw * 8192 + lrow * 128;
#pragma unroll
          for (int j = 0; j < BN / 8; j += 2) {
            const int cc = j + (lane >> 4);
            uint32_t hr[4];
#pragma unroll
            for (int u = 0; u < 2; u++) {
              float2 sb, cb;
              asm volatile("ld.shared.v2.f32 {%0, %1}, [%2];" : "=f"(sb.x), "=f"(sb.y) : "r"(s_gate + 512 + ((j + u) * 8 + cq) * 4));
              asm volatile("ld.shared.v2.f32 {%0, %1}, [%2];" : "=f"(cb.x), "=f"(cb.y) : "r"(s_gate + 1024 + ((j + u) * 8 + cq) * 4));
              const float* a = acc + (j + u) * 4;
              hr[2 * u] = pack_bf16((a[0] - mean[0]) * rstd[0] * cb.x + sb.x, (a[1] - mean[0]) * rstd[0] * cb.y + sb.y);
              hr[2 * u + 1] = pack_bf16((a[2] - mean[1]) * rstd[1] * cb.x + sb.x, (a[3] - mean[1]) * rstd[1] * cb.y + sb.y);
            }
            stsm_x4(hbase + (cc >> 3) * 16384 + (((cc & 7) ^ (lrow & 7)) << 4), hr);
          }
          fence_proxy_async();
          nbar_sync(2 + cw, 128);
          if ((tid & 127) == 0) {
#pragma unroll
            for (int h = 0; h < BN / 64; h++) tma_store_2d(&tmH, smem_base + h * 16384 + cw * 8192, n0 + h * 64, m0 + cw * 64);
            bulk_commit();
          }
        }
        if ((tid & 127) == 0) bulk_wait_all();
      }
      if (tid == 128) TSTAMP(EPI, 3 + 3 * t);
    };
    tile(IntC<C::BN>{}, IntC<0>{});
    if constexpr (C::BN2 != 0) tile(IntC<C::BN2>{}, IntC<1>{});
  }
}

constexpr int AT_STAGES = 10;
#define AT_LOOK 3
constexpr int AT_KBYTES = 128 * 64;
constexpr int AT_VBYTES = 5 * 1024;
constexpr int AT_STAGE_BYTES = AT_KBYTES + 2 * AT_VBYTES;
constexpr int AT_QBYTES = 512 * 64;
constexpr int AT_SMEM = AT_QBYTES + AT_STAGES * AT_STAGE_BYTES + 1024 + 512;
constexpr float SOFTMAX_C = 0.17677669529663687f * 1.4426950408889634f;
constexpr float SC_MUFU = SOFTMAX_C * 1048576.f;
constexpr float SC_FIX = SOFTMAX_C * 1.88079096131566e-37f;
#define POLY_MASK 0x5555

__device__ __noinline__ void attn_slow_row(int row, int c) {
  float q[32];
  for (int v = 0; v < 32; v++) q[v] = __bfloat162float(g_q[qk_idx(row, v)]);
  float m = -INFINITY, l = 0.f, o[8];
  for (int j = 0; j < 8; j++) o[j] = 0.f;
  for (int key = 0; key < SEQ; key++) {
    float s = 0.f;
    for (int v = 0; v < 32; v++) s += q[v] * __bfloat162float(g_k[qk_idx(key, v)]);
    s *= SC_MUFU;
    const float mn = fmaxf(m, s);
    const float sc = exp2f(m - mn), p = exp2f(s - mn);
    m = mn;
    l = l * sc + p;
    for (int j = 0; j < 4; j++) {
      o[2 * j] = o[2 * j] * sc + p * __bfloat162float(g_vt[vt_idx(j * 8 + 2 * c, key)]);
      o[2 * j + 1] = o[2 * j + 1] * sc + p * __bfloat162float(g_vt[vt_idx(j * 8 + 2 * c + 1, key)]);
    }
  }
  *(reinterpret_cast<uint4*>(g_o) + (size_t)row * 4 + c) = make_uint4(pack_bf16(o[0] / l, o[1] / l), pack_bf16(o[2] / l, o[3] / l),
                                                                      pack_bf16(o[4] / l, o[5] / l), pack_bf16(o[6] / l, o[7] / l));
}

__device__ __forceinline__ uint32_t fma_bf16x2(uint32_t a, uint32_t b, uint32_t c) {
  uint32_t r;
  asm("fma.rn.bf16x2 %0, %1, %2, %3;" : "=r"(r) : "r"(a), "r"(b), "r"(c));
  return r;
}
__device__ __forceinline__ uint32_t exp2_pair_fma(float s0, float s1, float fb) {
  float t0, t1;
  asm("fma.rn.sat.f32 %0, %1, %2, %3;" : "=f"(t0) : "f"(s0), "f"(SC_FIX), "f"(fb));
  asm("fma.rn.sat.f32 %0, %1, %2, %3;" : "=f"(t1) : "f"(s1), "f"(SC_FIX), "f"(fb));
  uint32_t w;
  asm("cvt.pack.sat.s16.s32 %0, %1, %2;" : "=r"(w) : "r"(__float_as_uint(t1)), "r"(__float_as_uint(t0)));
  uint32_t m;
  asm("lop3.b32 %0, %1, %2, %3, 0xEA;" : "=r"(m) : "r"(w), "r"(0x007F007Fu), "r"(0x3F803F80u));
  const uint32_t z = fma_bf16x2(m, 0x3EF83EF8u, 0xBF38BF38u);
  const uint32_t c = fma_bf16x2(z, z, 0xBD70BD70u);
  return fma_bf16x2(w, c, w);
}

struct AttnBlk {
  float o[20];
  float nm[2];
};
__device__ __forceinline__ void attn_set_ref(AttnBlk& b, int h, float m) { b.nm[h] = -m; }
__device__ __forceinline__ void attn_exps(const float (&s)[32], uint32_t (&p)[16], const AttnBlk& b) {
  const float fb[2] = {fmaf(b.nm[0], __uint_as_float(0x80u), __uint_as_float(0x3F80u)),
                       fmaf(b.nm[1], __uint_as_float(0x80u), __uint_as_float(0x3F80u))};
#pragma unroll
  for (int j = 0; j < 16; j++) {
    if ((POLY_MASK >> j) & 1) p[j] = exp2_pair_fma(s[2 * j], s[2 * j + 1], fb[j & 1]);
    else p[j] = pack_bf16(ex2(fmaf(s[2 * j], SC_MUFU, b.nm[j & 1])), ex2(fmaf(s[2 * j + 1], SC_MUFU, b.nm[j & 1])));
  }
}
__device__ __forceinline__ void attn_rescale(AttnBlk& b) {
  {
#pragma unroll
    for (int h = 0; h < 2; h++) {
      const float l = b.o[16 + 2 * h];
      if (l >= 65536.f && l < 1.329228e36f) {
        const int e = (int)(__float_as_uint(l) >> 23) - 127;
        const float sc = __uint_as_float((uint32_t)(127 - e) << 23);
        attn_set_ref(b, h, (float)e - b.nm[h]);
#pragma unroll
        for (int j = 0; j < 5; j++) { b.o[j * 4 + 2 * h] *= sc; b.o[j * 4 + 2 * h + 1] *= sc; }
      }
    }
  }
}
__device__ __forceinline__ void attn_qk(float (&s)[32], uint64_t dq, uint64_t dk) {
  wgmma_ss_z_n64_t0(s, dq, dk);
  wgmma_ss_n64_t0(s, dq + 2, dk + 2, 1);
}
__device__ __forceinline__ void attn_pv(const uint32_t (&p)[16], AttnBlk& b, uint64_t dv) {
#pragma unroll
  for (int kk = 0; kk < 4; kk++) wgmma_rs_n40_t0(b.o, p[kk * 4 + 0], p[kk * 4 + 1], p[kk * 4 + 2], p[kk * 4 + 3], dv + kk * 2, 1);
}
__device__ __forceinline__ void attn_init_ref(const float (&s)[32], AttnBlk& b) {
  float m0 = s[0], m1 = s[2];
#pragma unroll
  for (int j = 0; j < 8; j++) {
    m0 = fmaxf(m0, fmaxf(s[j * 4 + 0], s[j * 4 + 1]));
    m1 = fmaxf(m1, fmaxf(s[j * 4 + 2], s[j * 4 + 3]));
  }
  m0 = fmaxf(m0, __shfl_xor_sync(0xffffffffu, m0, 1)); m0 = fmaxf(m0, __shfl_xor_sync(0xffffffffu, m0, 2));
  m1 = fmaxf(m1, __shfl_xor_sync(0xffffffffu, m1, 1)); m1 = fmaxf(m1, __shfl_xor_sync(0xffffffffu, m1, 2));
  attn_set_ref(b, 0, rintf(m0 * SC_MUFU));
  attn_set_ref(b, 1, rintf(m1 * SC_MUFU));
}

__global__ void __launch_bounds__(512, 1)
    attn_kernel(const bf16* __restrict__ wo, const bf16* __restrict__ w1,
                const bf16* __restrict__ w2, const bf16* __restrict__ cvec, const bf16* __restrict__ wmod) {
  extern __shared__ uint8_t smem_raw[];
  if (blockIdx.x < 4) {
    pdl_launch();
    mod_rest(blockIdx.x, cvec, wmod, reinterpret_cast<float*>(smem_raw));
    return;
  }
  const int bid = blockIdx.x - 4;
  const uint32_t sq = (smem_u32(smem_raw) + 1023) & ~1023u;
  const uint32_t skv = sq + AT_QBYTES;
  const uint32_t bar_base = skv + AT_STAGES * AT_STAGE_BYTES;
  auto full_bar = [&](int s) { return bar_base + s * 8; };
  auto empty_bar = [&](int s) { return bar_base + (AT_STAGES + s) * 8; };
  const int tid = threadIdx.x, warp = tid >> 5, lane = tid & 31;
  const int wg = __shfl_sync(0xffffffffu, tid >> 7, 0);
  constexpr int NG = SEQ / 128;
  constexpr int NREFILL = NG - AT_STAGES;

  if (tid == 0) {
    TSTAMP(4, 0);
    for (int s = 0; s < AT_STAGES; s++) mbar_init(full_bar(s), 1);
    for (int s = 0; s < NREFILL; s++) mbar_init(empty_bar(s), 16);
    fence_barrier_init();
  }
  for (int i = tid; i < AT_STAGES * 128; i += 512) {
    const uint32_t a = skv + (i >> 7) * AT_STAGE_BYTES + AT_KBYTES + ((i >> 6) & 1) * AT_VBYTES + 4096 + (i & 63) * 16;
    asm volatile("st.shared.v4.b32 [%0], {%1, %1, %1, %1};" ::"r"(a), "r"(0x3F803F80u) : "memory");
  }
  fence_proxy_async();
  __syncthreads();
  pdl_launch();
  pdl_wait();
  if (tid == 0) TSTAMP(4, 4);

  auto load_kv = [&](int st, int g) {
    const uint32_t sk = skv + st * AT_STAGE_BYTES;
    mbar_expect_tx(full_bar(st), AT_KBYTES + 2 * 4096 + (g == 0 ? AT_QBYTES : 0));
    bulk_load(sk, g_k + g * 4096, AT_KBYTES, full_bar(st));
    if (g == 0) {
#pragma unroll
      for (int i = 0; i < 4; i++) bulk_load(sq + i * 8192, g_q + (size_t)bid * 16384 + i * 4096, 8192, full_bar(0));
    }
    bulk_load(sk + AT_KBYTES, g_vt + g * 4096, 4096, full_bar(st));
    bulk_load(sk + AT_KBYTES + AT_VBYTES, g_vt + g * 4096 + 2048, 4096, full_bar(st));
  };
  if (tid == 0) {
    load_kv(0, 0);
#pragma unroll 1
    for (int s = 1; s < AT_LOOK; s++) load_kv(s, s);
  }
  const int c = lane & 3;
  const int row0 = bid * 512 + wg * 128 + (warp & 3) * 16 + (lane >> 2);
  AttnBlk b0, b1;
#pragma unroll
  for (int i = 0; i < 20; i++) { b0.o[i] = 0.f; b1.o[i] = 0.f; }
  float s[32];
  uint32_t p[16];
  const uint64_t dq0 = make_desc(sq + wg * 128 * 64, 16, 512, 2), dq1 = dq0 + (64 * 64 >> 4);
  const uint64_t dk0 = make_desc(skv, 16, 512, 2), dv0 = make_desc(skv + AT_KBYTES, 16, 1024, 1);
  mbar_wait(full_bar(0), 0);
  if (tid == 0) TSTAMP(4, 1);
  wgmma_fence();
  attn_qk(s, dq1, dk0);
  wgmma_commit();
  wgmma_wait<0>();
  fence_regs(s);
  attn_init_ref(s, b1);
  wgmma_fence();
  attn_qk(s, dq0, dk0);
  wgmma_commit();
  wgmma_wait<0>();
  fence_regs(s);
  attn_init_ref(s, b0);

  auto half = [&](AttnBlk& b, uint64_t dq, uint64_t dk, uint64_t dv) {
    attn_exps(s, p, b);
    wgmma_fence();
    attn_qk(s, dq, dk);
    attn_pv(p, b, dv);
    wgmma_commit();
  };
  auto done = [&](AttnBlk& b) {
    wgmma_wait<0>();
    fence_regs(s);
    fence_regs(b.o);
  };
  int slot = 0;
#pragma unroll 1
  for (int g = 0; g < NG; g++) {
    const uint64_t off = (uint64_t)(slot * (AT_STAGE_BYTES >> 4));
    int nslot = slot + 1;
    if (nslot == AT_STAGES) nslot = 0;
    if (!(fmaxf(fmaxf(b0.o[16], b0.o[18]), fmaxf(b1.o[16], b1.o[18])) < 65536.f)) {
      attn_rescale(b0);
      attn_rescale(b1);
    }
    half(b0, dq1, dk0 + off, dv0 + off);
    if (tid == ((g & 3) << 7) && g + AT_LOOK < NG) {
      const int gn = g + AT_LOOK;
      if (gn >= AT_STAGES) mbar_wait(empty_bar(gn - AT_STAGES), 0);
      load_kv(gn >= AT_STAGES ? gn - AT_STAGES : gn, gn);
    }
  if (warp == 1 && g == 1) {
    constexpr int CH = DM * DM / 128 / 2, CF = DM * DFF / 128 / 7;
    if (lane < 2) l2_prefetch(wo + (size_t)(bid * 2 + lane) * CH, CH * 2);
    else if (lane < 9) l2_prefetch(w1 + (size_t)(bid * 7 + lane - 2) * CF, CF * 2);
    else if (lane < 16) l2_prefetch(w2 + (size_t)(bid * 7 + lane - 9) * CF, CF * 2);
  }
    done(b0);
    half(b1, dq0, dk0 + off + (64 * 64 >> 4), dv0 + off);
    done(b1);
    half(b0, dq1, dk0 + off + (64 * 64 >> 4), dv0 + off + (AT_VBYTES >> 4));
    if (g + 1 < NG) mbar_wait(full_bar(nslot), g + 1 >= AT_STAGES ? 1 : 0);
    done(b0);
    half(b1, dq0, dk0 + (uint64_t)(nslot * (AT_STAGE_BYTES >> 4)), dv0 + off + (AT_VBYTES >> 4));
    done(b1);
    if (g < NREFILL && lane == 0) mbar_arrive(empty_bar(g));
    slot = nslot;
  }
  if (tid == 0) TSTAMP(4, 2);
  uint32_t redo = 0;
  auto store = [&](AttnBlk& b, int blk) {
#pragma unroll
    for (int h = 0; h < 2; h++) {
      const int row = row0 + blk * 64 + h * 8;
      const float l = b.o[16 + 2 * h];
      if (!(l < 1.329228e36f) || !(l > 0.f)) redo |= 1u << (blk * 2 + h);
      const float inv = 1.0f / l;
      *(reinterpret_cast<uint4*>(g_o) + (size_t)row * 4 + c) =
          make_uint4(pack_bf16(b.o[2 * h] * inv, b.o[2 * h + 1] * inv), pack_bf16(b.o[4 + 2 * h] * inv, b.o[5 + 2 * h] * inv),
                     pack_bf16(b.o[8 + 2 * h] * inv, b.o[9 + 2 * h] * inv), pack_bf16(b.o[12 + 2 * h] * inv, b.o[13 + 2 * h] * inv));
    }
  };
  store(b0, 0);
  store(b1, 1);
  if (redo) {
#pragma unroll 1
    for (int i = 0; i < 4; i++)
      if ((redo >> i) & 1) attn_slow_row(row0 + (i >> 1) * 64 + (i & 1) * 8, c);
  }
  if (tid == 0) TSTAMP(4, 3);
}

typedef CUresult (*EncodeFn)(CUtensorMap*, CUtensorMapDataType, cuuint32_t, void*, const cuuint64_t*, const cuuint64_t*,
                             const cuuint32_t*, const cuuint32_t*, CUtensorMapInterleave, CUtensorMapSwizzle,
                             CUtensorMapL2promotion, CUtensorMapFloatOOBfill);

EncodeFn g_encode = nullptr;

CUtensorMap make_map(const void* ptr, int rank, const cuuint64_t* dims, const cuuint64_t* strides, const cuuint32_t* box,
                     CUtensorMapSwizzle swz) {
  CUtensorMap m;
  cuuint32_t es[5] = {1, 1, 1, 1, 1};
  g_encode(&m, CU_TENSOR_MAP_DATA_TYPE_BFLOAT16, rank, const_cast<void*>(ptr), dims, strides, box, es,
           CU_TENSOR_MAP_INTERLEAVE_NONE, swz, CU_TENSOR_MAP_L2_PROMOTION_L2_256B, CU_TENSOR_MAP_FLOAT_OOB_FILL_NONE);
  return m;
}
CUtensorMap map2d(const void* ptr, int rows, int cols, int br, int bc, CUtensorMapSwizzle swz) {
  cuuint64_t dims[2] = {(cuuint64_t)cols, (cuuint64_t)rows};
  cuuint64_t strides[1] = {(cuuint64_t)cols * 2};
  cuuint32_t box[2] = {(cuuint32_t)bc, (cuuint32_t)br};
  return make_map(ptr, 2, dims, strides, box, swz);
}
CUtensorMap mapBperm(const void* ptr, int K, int N) {
  cuuint64_t dims[5] = {(cuuint64_t)N, 2, 4, 4, (cuuint64_t)(K / 32)};
  cuuint64_t strides[4] = {(cuuint64_t)N * 2, (cuuint64_t)N * 16, (cuuint64_t)N * 4, (cuuint64_t)N * 64};
  cuuint32_t box[5] = {64, 2, 4, 4, 2};
  return make_map(ptr, 5, dims, strides, box, CU_TENSOR_MAP_SWIZZLE_128B);
}

template <class K, class... Args>
void launch(K kern, dim3 grid, dim3 block, int smem, dim3 cluster, bool pdl, Args... args) {
  cudaLaunchConfig_t cfg = {};
  cfg.gridDim = grid;
  cfg.blockDim = block;
  cfg.dynamicSmemBytes = smem;
  cfg.stream = cudaStreamPerThread;
  cudaLaunchAttribute at[2];
  int n = 0;
  if (cluster.x * cluster.y * cluster.z > 1) {
    at[n].id = cudaLaunchAttributeClusterDimension;
    at[n].val.clusterDim.x = cluster.x; at[n].val.clusterDim.y = cluster.y; at[n].val.clusterDim.z = cluster.z;
    n++;
  }
  if (pdl) {
    at[n].id = cudaLaunchAttributeProgrammaticStreamSerialization;
    at[n].val.programmaticStreamSerializationAllowed = 1;
    n++;
  }
  cfg.attrs = at;
  cfg.numAttrs = n;
  cudaLaunchKernelEx(&cfg, kern, args...);
}

#define QKV_ST 5
#define OP_ST 6
#define F1_ST 4
#define F2_ST 6
typedef GemmCfg<128, 0, QKV_ST, EPI_QKV, DM> CfgQKV;
typedef GemmCfg<128, 0, OP_ST, EPI_OPROJ, DM> CfgOP;
typedef GemmCfg<256, 192, F1_ST, EPI_FFN1, DM> CfgF1;
typedef GemmCfg<128, 0, F2_ST, EPI_FFN2, DFF> CfgF2;

struct Maps {
  CUtensorMap h_a, wq_b, o_a, wo_b, h2_a, w1_b, hff_a, w2_b, x_r, x1_r, out_w, h_w;
  const void* key[11];
  bool valid;
};
Maps g_maps;

}

extern "C" void kernel_launch(void* const* d_in, const int* in_sizes, int n_in, void* d_out, int out_size) {
  const bf16* x = (const bf16*)d_in[0];
  const bf16* wq = (const bf16*)d_in[1];
  const bf16* wk = (const bf16*)d_in[2];
  const bf16* wv = (const bf16*)d_in[3];
  const bf16* wo = (const bf16*)d_in[4];
  const bf16* w1 = (const bf16*)d_in[6];
  const bf16* w2 = (const bf16*)d_in[7];
  const bf16* c = (const bf16*)d_in[8];
  const bf16* wmod = (const bf16*)d_in[9];
  bf16* out = (bf16*)d_out;

  bool same = g_maps.valid;
  for (int i = 0; i < 10 && same; i++) same = g_maps.key[i] == d_in[i];
  same = same && g_maps.key[10] == d_out;
  if (!same) {
    if (!g_encode) {
      cudaDriverEntryPointQueryResult qr;
      void* fn = nullptr;
      cudaGetDriverEntryPoint("cuTensorMapEncodeTiled", &fn, cudaEnableDefault, &qr);
      g_encode = (EncodeFn)fn;
    }
    void *ph, *po, *phff, *px1;
    cudaGetSymbolAddress(&px1, g_x1);
    cudaGetSymbolAddress(&ph, g_h);
    cudaGetSymbolAddress(&po, g_o);
    cudaGetSymbolAddress(&phff, g_hff);
    g_maps.h_a = map2d(ph, SEQ, DM, 128, 64, CU_TENSOR_MAP_SWIZZLE_128B);
    g_maps.wq_b = map2d(wq, DM, DM, 64, 64, CU_TENSOR_MAP_SWIZZLE_128B);
    g_maps.o_a = map2d(po, SEQ, DM, 128, 64, CU_TENSOR_MAP_SWIZZLE_128B);
    g_maps.wo_b = map2d(wo, DM, DM, 64, 64, CU_TENSOR_MAP_SWIZZLE_128B);
    g_maps.h2_a = g_maps.h_a;
    g_maps.w1_b = map2d(w1, DM, DFF, 64, 64, CU_TENSOR_MAP_SWIZZLE_128B);
    g_maps.hff_a = map2d(phff, SEQ, DFF, 128, 64, CU_TENSOR_MAP_SWIZZLE_128B);
    g_maps.w2_b = mapBperm(w2, DFF, DM);
    g_maps.x_r = map2d(x, SEQ, DM, 64, 64, CU_TENSOR_MAP_SWIZZLE_128B);
    g_maps.x1_r = map2d(px1, SEQ, DM, 64, 64, CU_TENSOR_MAP_SWIZZLE_128B);
    g_maps.out_w = map2d(out, SEQ, DM, 64, 64, CU_TENSOR_MAP_SWIZZLE_128B);
    g_maps.h_w = map2d(ph, SEQ, DM, 64, 64, CU_TENSOR_MAP_SWIZZLE_128B);
    g_maps.key[10] = d_out;
    for (int i = 0; i < 10; i++) g_maps.key[i] = d_in[i];
    g_maps.valid = true;
    cudaFuncSetAttribute(gemm_kernel<CfgQKV>, cudaFuncAttributeMaxDynamicSharedMemorySize, CfgQKV::SMEM);
    cudaFuncSetAttribute(gemm_kernel<CfgOP>, cudaFuncAttributeMaxDynamicSharedMemorySize, CfgOP::SMEM);
    cudaFuncSetAttribute(gemm_kernel<CfgF1>, cudaFuncAttributeMaxDynamicSharedMemorySize, CfgF1::SMEM);
    cudaFuncSetAttribute(gemm_kernel<CfgF2>, cudaFuncAttributeMaxDynamicSharedMemorySize, CfgF2::SMEM);
    cudaFuncSetAttribute(attn_kernel, cudaFuncAttributeMaxDynamicSharedMemorySize, AT_SMEM);
  }
  const dim3 one(1, 1, 1);
#define PDL true
  pre_kernel<<<128, 512, 0, cudaStreamPerThread>>>(c, wmod, x);
  launch(gemm_kernel<CfgQKV>, dim3(8, 16), dim3(384), CfgQKV::SMEM, one, PDL, g_maps.h_a, g_maps.wq_b, g_maps.x_r, g_maps.x_r, g_maps.h_w, wk, wv);
  launch(attn_kernel, dim3(132), dim3(512), AT_SMEM, one, PDL, wo, w1, w2, c, wmod);
  launch(gemm_kernel<CfgOP>, dim3(8, 16), dim3(384), CfgOP::SMEM, one, PDL, g_maps.o_a, g_maps.wo_b, g_maps.x_r, g_maps.x1_r, g_maps.h_w, wk, wv);
  launch(gemm_kernel<CfgF1>, dim3(8, 16), dim3(384), CfgF1::SMEM, one, PDL, g_maps.h2_a, g_maps.w1_b, g_maps.x_r, g_maps.x_r, g_maps.h_w, wk, wv);
  launch(gemm_kernel<CfgF2>, dim3(8, 16), dim3(384), CfgF2::SMEM, one, PDL, g_maps.hff_a, g_maps.w2_b, g_maps.x1_r, g_maps.out_w, g_maps.h_w, wk, wv);
}
```
